```python
import torch

def _softmax(x, axis=-1):
    return torch.softmax(x, dim=axis)

def _gelu(x):
    return torch.nn.functional.gelu(x, approximate='tanh')

def _silu(x):
    return torch.nn.functional.silu(x)

def _sigmoid(x):
    return torch.sigmoid(x)

def _layernorm(x, axis=-1, eps=1e-05):
    m = x.mean(dim=axis, keepdim=True)
    v = x.var(dim=axis, keepdim=True, unbiased=False)
    return (x - m) / torch.sqrt(v + eps)

def _scatter_add(tgt, idx, src, axis=0):
    return tgt.clone().index_add_(axis, idx, src)

def _segment_sum(src, seg, n):
    out = torch.zeros((n,) + src.shape[1:], dtype=src.dtype)
    return out.index_add_(0, seg, src)

def _pad(x, pw):
    flat = tuple((v for pair in reversed(pw) for v in pair))
    return torch.nn.functional.pad(x, flat)
kernel_name = 'concat_heads__grouped_kv_mqa__memory_aug_recurrent_mem_tr__prompt'

def setup_inputs():

    _w = lambda a: (lambda t: t.to(torch.bfloat16) if t.is_floating_point() else t)(torch.as_tensor(a))

    def _A_setup():
        B, S, D, H = (1, 2048, 512, 32)
        Dh = D // H
        return {'x': _w((lambda *s: torch.randn(*s, dtype=torch.bfloat16) * 0.05)(B, S, D)), 'wq': _w((lambda *s: torch.randn(*s, dtype=torch.bfloat16) * 1.6)(D, H * Dh)), 'wk': _w((lambda *s: torch.randn(*s, dtype=torch.bfloat16) * 1.6)(D, Dh)), 'wv': _w((lambda *s: torch.randn(*s, dtype=torch.bfloat16) * 0.1)(D, Dh)), 'wo': _w((lambda *s: torch.randn(*s, dtype=torch.bfloat16) * 0.1)(H * Dh, D))}
    _A_in = _A_setup()

    def _B_setup():
        B, S, Dm = (1, 2048, 512)
        H, Dh = (32, 128)
        M, seg = (8, 32)
        seg = min(seg, S)
        S = S // seg * seg
        return {'x': _w((lambda *s: torch.randn(*s, dtype=torch.bfloat16) * 0.05)(B, S, Dm)), 'mem0': _w((lambda *s: torch.randn(*s, dtype=torch.bfloat16) * 0.8)(B, M, Dm)), 'Wq': _w((lambda *s: torch.randn(*s, dtype=torch.bfloat16) * 3.2)(Dm, H, Dh) * Dm ** (-0.5)), 'Wk': _w((lambda *s: torch.randn(*s, dtype=torch.bfloat16) * 3.2)(Dm, H, Dh) * Dm ** (-0.5)), 'Wv': _w((lambda *s: torch.randn(*s, dtype=torch.bfloat16) * 0.8)(Dm, H, Dh) * Dm ** (-0.5)), 'Wo': _w((lambda *s: torch.randn(*s, dtype=torch.bfloat16) * 0.8)(H, Dh, Dm) * (H * Dh) ** (-0.5)), 'seg_len': seg}
    _B_in = _B_setup()
    return {'A_x': _A_in['x'], 'A_wq': _A_in['wq'], 'A_wk': _A_in['wk'], 'A_wv': _A_in['wv'], 'A_wo': _A_in['wo'], 'B_x': _B_in['x'], 'B_mem0': _B_in['mem0'], 'B_Wq': _B_in['Wq'], 'B_Wk': _B_in['Wk'], 'B_Wv': _B_in['Wv'], 'B_Wo': _B_in['Wo'], 'B_seg_len': _B_in['seg_len']}

def reference(A_x, A_wq, A_wk, A_wv, A_wo, B_x, B_mem0, B_Wq, B_Wk, B_Wv, B_Wo, B_seg_len):

    def _A_ref(x, wq, wk, wv, wo):
        B, S, D = x.shape
        H = 32
        Dh = D // H
        q = (lambda x, *d: x.permute(*d))((x @ wq).reshape(B, S, H, Dh), 0, 2, 1, 3)
        k = x @ wk
        v = x @ wv
        scores = torch.einsum('bhqd,bkd->bhqk', q, k) * Dh ** (-0.5)
        p = _softmax(scores, axis=-1)
        o = torch.einsum('bhqk,bkd->bhqd', p, v)
        return (lambda x, *d: x.permute(*d))(o, 0, 2, 1, 3).reshape(B, S, H * Dh) @ wo

    def _B_ref(x, mem0, Wq, Wk, Wv, Wo, seg_len):
        B, S, Dm = x.shape
        H, Dh = (Wq.shape[1], Wq.shape[2])
        M = mem0.shape[1]
        scale = Dh ** (-0.5)
        n_seg = S // seg_len
        L = M + seg_len
        idx = torch.arange(L)
        mask = (idx[:, None] < M) | (idx[:, None] >= idx[None, :])
        mem = mem0
        outs = []
        for s in range(n_seg):
            xs = x[:, s * seg_len:(s + 1) * seg_len, :].clone()
            h = torch.concatenate([mem, xs], axis=1)
            q = torch.einsum('btd,dhe->bhte', h, Wq)
            k = torch.einsum('btd,dhe->bhte', h, Wk)
            v = torch.einsum('btd,dhe->bhte', h, Wv)
            scores = torch.einsum('bhqe,bhke->bhqk', q, k) * scale
            scores = torch.where(mask[None, None], scores, -1000000000.0)
            p = _softmax(scores, axis=-1)
            o = torch.einsum('bhqk,bhke->bhqe', p, v)
            o = torch.einsum('bhte,hed->btd', o, Wo)
            mem = o[:, :M, :].clone()
            outs.append(o[:, M:, :])
        return torch.concatenate(outs, axis=1)
    a = _A_ref(A_x, A_wq, A_wk, A_wv, A_wo)
    b = _B_ref(B_x, B_mem0, B_Wq, B_Wk, B_Wv, B_Wo, B_seg_len)
    return torch.concatenate([a, b], axis=-1)
```

```cpp
#include <cuda_runtime.h>
#include <cuda_bf16.h>
#include <stdint.h>

typedef __nv_bfloat16 bf16;
constexpr int SPIN_LIMIT = 1 << 18;

__device__ __align__(1024) bf16 g_qkvx[3 * 64 * 32 * 32 * 128];
__device__ __align__(1024) bf16 g_ox[2048 * 4096];
__device__ __align__(1024) uint4 g_part[128 * 512];
__device__ __align__(1024) uint4 g_memll[1024];
__device__ __align__(1024) uint4 g_xch[128 * 192];
__device__ unsigned g_pflag[3 * 16 * 32];
__device__ unsigned g_epoch;
__device__ __align__(1024) bf16 g_qa[2048 * 512];
__device__ __align__(1024) bf16 g_ka[2048 * 16];
__device__ __align__(1024) bf16 g_va[2048 * 16];
__device__ __align__(1024) bf16 g_oa[2048 * 512];

__device__ __forceinline__ uint32_t smem_u32(const void* p) { return (uint32_t)__cvta_generic_to_shared(p); }

__device__ __forceinline__ void ldsm_x4(uint32_t& r0, uint32_t& r1, uint32_t& r2, uint32_t& r3, uint32_t a) {
    asm volatile("ldmatrix.sync.aligned.m8n8.x4.shared.b16 {%0,%1,%2,%3}, [%4];"
                 : "=r"(r0), "=r"(r1), "=r"(r2), "=r"(r3) : "r"(a) : "memory");
}
__device__ __forceinline__ void ldsm_x4_t(uint32_t& r0, uint32_t& r1, uint32_t& r2, uint32_t& r3, uint32_t a) {
    asm volatile("ldmatrix.sync.aligned.m8n8.x4.trans.shared.b16 {%0,%1,%2,%3}, [%4];"
                 : "=r"(r0), "=r"(r1), "=r"(r2), "=r"(r3) : "r"(a) : "memory");
}
__device__ __forceinline__ void ldsm_x2(uint32_t& r0, uint32_t& r1, uint32_t a) {
    asm volatile("ldmatrix.sync.aligned.m8n8.x2.shared.b16 {%0,%1}, [%2];" : "=r"(r0), "=r"(r1) : "r"(a) : "memory");
}
__device__ __forceinline__ void ldsm_x2_t(uint32_t& r0, uint32_t& r1, uint32_t a) {
    asm volatile("ldmatrix.sync.aligned.m8n8.x2.trans.shared.b16 {%0,%1}, [%2];" : "=r"(r0), "=r"(r1) : "r"(a) : "memory");
}
__device__ __forceinline__ void mma16816(float* c, const uint32_t* a, uint32_t b0, uint32_t b1) {
    asm volatile("mma.sync.aligned.m16n8k16.row.col.f32.bf16.bf16.f32 {%0,%1,%2,%3}, {%4,%5,%6,%7}, {%8,%9}, {%0,%1,%2,%3};"
                 : "+f"(c[0]), "+f"(c[1]), "+f"(c[2]), "+f"(c[3])
                 : "r"(a[0]), "r"(a[1]), "r"(a[2]), "r"(a[3]), "r"(b0), "r"(b1));
}
__device__ __forceinline__ void cp_async16(uint32_t dst, const void* src) {
    asm volatile("cp.async.cg.shared.global [%0], [%1], 16;" ::"r"(dst), "l"(src) : "memory");
}
__device__ __forceinline__ void cp_async_commit() { asm volatile("cp.async.commit_group;" ::: "memory"); }
template <int N> __device__ __forceinline__ void cp_async_wait() { asm volatile("cp.async.wait_group %0;" ::"n"(N) : "memory"); }

__device__ __forceinline__ uint4 ld_relaxed_v4(const uint4* p) {
    uint4 v;
    asm volatile("ld.relaxed.gpu.global.v4.u32 {%0,%1,%2,%3}, [%4];" : "=r"(v.x), "=r"(v.y), "=r"(v.z), "=r"(v.w) : "l"(p) : "memory");
    return v;
}
__device__ __forceinline__ void st_relaxed_v4(uint4* p, uint32_t x, uint32_t y, uint32_t z, uint32_t w) {
    asm volatile("st.relaxed.gpu.global.v4.u32 [%0], {%1,%2,%3,%4};" ::"l"(p), "r"(x), "r"(y), "r"(z), "r"(w) : "memory");
}
__device__ __forceinline__ unsigned ld_acquire_u32(const unsigned* p) {
    unsigned v;
    asm volatile("ld.acquire.gpu.global.u32 %0, [%1];" : "=r"(v) : "l"(p) : "memory");
    return v;
}
__device__ __forceinline__ void st_release_u32(unsigned* p, unsigned v) {
    asm volatile("st.release.gpu.global.u32 [%0], %1;" ::"l"(p), "r"(v) : "memory");
}
__device__ __forceinline__ uint32_t mapa(uint32_t a, uint32_t r) {
    uint32_t o;
    asm volatile("mapa.shared::cluster.u32 %0, %1, %2;" : "=r"(o) : "r"(a), "r"(r));
    return o;
}
__device__ __forceinline__ void st_async_b32(uint32_t dst, uint32_t v, uint32_t mbar) {
    asm volatile("st.async.weak.shared::cluster.mbarrier::complete_tx::bytes.b32 [%0], %1, [%2];" ::"r"(dst), "r"(v), "r"(mbar) : "memory");
}
__device__ __forceinline__ void mbar_wait(uint32_t a, uint32_t par) {
    uint32_t ok = 0;
    int it = 0;
    while (!ok && it < SPIN_LIMIT) {
        asm volatile("{.reg .pred p; mbarrier.try_wait.parity.shared::cta.b64 p, [%1], %2; selp.u32 %0,1,0,p;}"
                     : "=r"(ok) : "r"(a), "r"(par) : "memory");
        it++;
    }
}
__device__ __forceinline__ uint32_t pack_bf16(float lo, float hi) {
    __nv_bfloat162 v = __floats2bfloat162_rn(lo, hi);
    return *reinterpret_cast<uint32_t*>(&v);
}
__device__ __forceinline__ float bf16r(float x) { return __bfloat162float(__float2bfloat16_rn(x)); }

struct GemmArgs {
    const bf16* A; int lda;
    const bf16* B0; const bf16* B1; const bf16* B2; int ldb;
    bf16* C; int ldc;
    int K;
    int finalize;
};

constexpr int GA_STRIDE = 40, GB_STRIDE = 136;
constexpr int G_STAGE = 128 * GA_STRIDE + 32 * GB_STRIDE;
constexpr int G_STAGES = 3;
constexpr int G_SMEM = G_STAGES * G_STAGE * 2;

template <int EPI>
__global__ void __launch_bounds__(256) gemm_kernel(GemmArgs g) {
    extern __shared__ __align__(16) unsigned char smem_raw[];
    bf16* sm = reinterpret_cast<bf16*>(smem_raw);
    const int tid = threadIdx.x, lane = tid & 31, warp = tid >> 5;
    const int wm = warp >> 2, wn = warp & 3;
    int bm, bn;
    const bf16* Bp;
    if (EPI == 1) {
        bm = blockIdx.x / 96; bn = blockIdx.x % 96;
        const int which = bn >> 5;
        Bp = (which == 0 ? g.B0 : (which == 1 ? g.B1 : g.B2)) + (bn & 31) * 128;
    } else {
        bm = blockIdx.y; bn = blockIdx.x;
        Bp = g.B0 + bn * 128;
    }
    const bf16* Ap = g.A + (size_t)bm * 128 * g.lda;
    const int nk = g.K / 32;

    auto load_stage = [&](int st, int kt) {
        bf16* sa = sm + st * G_STAGE;
        bf16* sb = sa + 128 * GA_STRIDE;
#pragma unroll
        for (int i = 0; i < 2; i++) {
            int c = tid + i * 256;
            int r = c >> 2, ch = c & 3;
            cp_async16(smem_u32(sa + r * GA_STRIDE + ch * 8), Ap + (size_t)r * g.lda + kt * 32 + ch * 8);
        }
#pragma unroll
        for (int i = 0; i < 2; i++) {
            int c = tid + i * 256;
            int r = c >> 4, ch = c & 15;
            cp_async16(smem_u32(sb + r * GB_STRIDE + ch * 8), Bp + (size_t)(kt * 32 + r) * g.ldb + ch * 8);
        }
    };

    float acc[4][4][4];
#pragma unroll
    for (int a = 0; a < 4; a++)
#pragma unroll
        for (int b = 0; b < 4; b++)
#pragma unroll
            for (int c = 0; c < 4; c++) acc[a][b][c] = 0.f;

#pragma unroll
    for (int s = 0; s < G_STAGES - 1; s++) {
        if (s < nk) load_stage(s, s);
        cp_async_commit();
    }
    for (int kt = 0; kt < nk; kt++) {
        cp_async_wait<G_STAGES - 2>();
        __syncthreads();
        {
            int nx = kt + G_STAGES - 1;
            if (nx < nk) load_stage(nx % G_STAGES, nx);
            cp_async_commit();
        }
        const bf16* sa = sm + (kt % G_STAGES) * G_STAGE;
        const bf16* sb = sa + 128 * GA_STRIDE;
#pragma unroll
        for (int ks = 0; ks < 2; ks++) {
            uint32_t af[4][4], bfr[4][2];
#pragma unroll
            for (int mt = 0; mt < 4; mt++) {
                int r = wm * 64 + mt * 16 + (lane & 7) + ((lane >> 3) & 1) * 8;
                int c = ks * 16 + (lane >> 4) * 8;
                ldsm_x4(af[mt][0], af[mt][1], af[mt][2], af[mt][3], smem_u32(sa + r * GA_STRIDE + c));
            }
#pragma unroll
            for (int np = 0; np < 2; np++) {
                int r = ks * 16 + (lane & 7) + ((lane >> 3) & 1) * 8;
                int c = wn * 32 + np * 16 + (lane >> 4) * 8;
                ldsm_x4_t(bfr[np * 2][0], bfr[np * 2][1], bfr[np * 2 + 1][0], bfr[np * 2 + 1][1], smem_u32(sb + r * GB_STRIDE + c));
            }
#pragma unroll
            for (int mt = 0; mt < 4; mt++)
#pragma unroll
                for (int nt = 0; nt < 4; nt++) mma16816(acc[mt][nt], af[mt], bfr[nt][0], bfr[nt][1]);
        }
    }
    cp_async_wait<0>();

    if (EPI == 0) {
#pragma unroll
        for (int mt = 0; mt < 4; mt++)
#pragma unroll
            for (int nt = 0; nt < 4; nt++) {
                int r = bm * 128 + wm * 64 + mt * 16 + (lane >> 2);
                int c = bn * 128 + wn * 32 + nt * 8 + (lane & 3) * 2;
                *reinterpret_cast<uint32_t*>(g.C + (size_t)r * g.ldc + c) = pack_bf16(acc[mt][nt][0], acc[mt][nt][1]);
                *reinterpret_cast<uint32_t*>(g.C + (size_t)(r + 8) * g.ldc + c) = pack_bf16(acc[mt][nt][2], acc[mt][nt][3]);
            }
        if (g.finalize && blockIdx.x == 0 && blockIdx.y == 0 && tid == 0) {
            g_epoch = g_epoch + 1;
        }
    } else {
        const int which = bn >> 5, h = bn & 31;
#pragma unroll
        for (int mt = 0; mt < 4; mt++)
#pragma unroll
            for (int nt = 0; nt < 4; nt++) {
#pragma unroll
                for (int hf = 0; hf < 2; hf++) {
                    int row = wm * 64 + mt * 16 + (lane >> 2) + hf * 8;
                    int seg = bm * 4 + (row >> 5), tok = row & 31;
                    int col = wn * 32 + nt * 8 + (lane & 3) * 2;
                    int chunk = (col >> 3) ^ (tok & 7);
                    bf16* dst = g_qkvx + ((((size_t)which * 64 + seg) * 32 + h) * 32 + tok) * 128 + chunk * 8 + (col & 7);
                    *reinterpret_cast<uint32_t*>(dst) = pack_bf16(acc[mt][nt][hf * 2], acc[mt][nt][hf * 2 + 1]);
                }
            }
        __threadfence();
        __syncthreads();
        if (tid == 0) {
            unsigned E = *(volatile unsigned*)&g_epoch;
            st_release_u32(&g_pflag[(which * 16 + bm) * 32 + h], E + 1);
        }
    }
}

constexpr int KV_SMEM = (512 * 32 + 32 * 520) * 2;
__global__ void __launch_bounds__(256) kv_a_kernel(const bf16* __restrict__ x, const bf16* __restrict__ wk, const bf16* __restrict__ wv) {
    extern __shared__ __align__(16) unsigned char smem_raw[];
    bf16* sw = reinterpret_cast<bf16*>(smem_raw);
    bf16* sx = sw + 512 * 32;
    const int tid = threadIdx.x;
    for (int i = tid; i < 512 * 2; i += 256) {
        int k = i >> 1, hf = i & 1;
        *reinterpret_cast<uint4*>(sw + k * 32 + hf * 8) = *reinterpret_cast<const uint4*>(wk + k * 16 + hf * 8);
        *reinterpret_cast<uint4*>(sw + k * 32 + 16 + hf * 8) = *reinterpret_cast<const uint4*>(wv + k * 16 + hf * 8);
    }
    const int t0 = blockIdx.x * 32;
    for (int i = tid; i < 32 * 64; i += 256) {
        int r = i >> 6, c = i & 63;
        *reinterpret_cast<uint4*>(sx + r * 520 + c * 8) = *reinterpret_cast<const uint4*>(x + (size_t)(t0 + r) * 512 + c * 8);
    }
    __syncthreads();
    const int r = tid >> 3, cg = tid & 7;
    float a0 = 0, a1 = 0, a2 = 0, a3 = 0;
#pragma unroll 8
    for (int k = 0; k < 512; k++) {
        float xv = __bfloat162float(sx[r * 520 + k]);
        uint2 w = *reinterpret_cast<const uint2*>(sw + k * 32 + cg * 4);
        __nv_bfloat162 w0 = *reinterpret_cast<__nv_bfloat162*>(&w.x), w1 = *reinterpret_cast<__nv_bfloat162*>(&w.y);
        a0 += xv * __low2float(w0); a1 += xv * __high2float(w0);
        a2 += xv * __low2float(w1); a3 += xv * __high2float(w1);
    }
    bf16* dst = (cg < 4 ? g_ka : g_va) + (size_t)(t0 + r) * 16 + (cg & 3) * 4;
    uint2 o; o.x = pack_bf16(a0, a1); o.y = pack_bf16(a2, a3);
    *reinterpret_cast<uint2*>(dst) = o;
}

constexpr int AK_CHUNK = 256;
__global__ void __launch_bounds__(256) attn_a_kernel() {
    __shared__ __align__(128) bf16 sk[2][AK_CHUNK * 16];
    __shared__ __align__(128) bf16 sv[2][AK_CHUNK * 16];
    const int tid = threadIdx.x, lane = tid & 31, warp = tid >> 5;
    const int qb = blockIdx.x >> 2, hg = blockIdx.x & 3;
    const int h = hg * 8 + warp;
    const int q0 = qb * 32;

    auto load_chunk = [&](int st, int c) {
#pragma unroll
        for (int i = 0; i < 2; i++) {
            int idx = tid + i * 256;
            int r = idx >> 1, ch = idx & 1;
            int pc = ch ^ ((r >> 2) & 1);
            cp_async16(smem_u32(&sk[st][r * 16 + pc * 8]), g_ka + (size_t)(c * AK_CHUNK + r) * 16 + ch * 8);
            cp_async16(smem_u32(&sv[st][r * 16 + pc * 8]), g_va + (size_t)(c * AK_CHUNK + r) * 16 + ch * 8);
        }
    };
    load_chunk(0, 0);
    cp_async_commit();

    uint32_t qf[2][4];
#pragma unroll
    for (int mt = 0; mt < 2; mt++) {
        const bf16* qp = g_qa + (size_t)(q0 + mt * 16 + (lane >> 2)) * 512 + h * 16 + (lane & 3) * 2;
        qf[mt][0] = *reinterpret_cast<const uint32_t*>(qp);
        qf[mt][1] = *reinterpret_cast<const uint32_t*>(qp + 8 * 512);
        qf[mt][2] = *reinterpret_cast<const uint32_t*>(qp + 8);
        qf[mt][3] = *reinterpret_cast<const uint32_t*>(qp + 8 * 512 + 8);
    }
    float o[2][2][4];
    float mx[2][2], sm_[2][2];
#pragma unroll
    for (int mt = 0; mt < 2; mt++) {
        mx[mt][0] = mx[mt][1] = -INFINITY;
        sm_[mt][0] = sm_[mt][1] = 0.f;
#pragma unroll
        for (int n = 0; n < 2; n++)
#pragma unroll
            for (int c = 0; c < 4; c++) o[mt][n][c] = 0.f;
    }
    const float SC = 0.25f * 1.4426950408889634f;
    constexpr int NCH = 2048 / AK_CHUNK;
    for (int c = 0; c < NCH; c++) {
        cp_async_wait<0>();
        __syncthreads();
        if (c + 1 < NCH) load_chunk((c + 1) & 1, c + 1);
        cp_async_commit();
        const bf16* kk = sk[c & 1];
        const bf16* vv = sv[c & 1];
#pragma unroll 1
        for (int sb = 0; sb < AK_CHUNK / 64; sb++) {
            float s[2][8][4];
#pragma unroll
            for (int np = 0; np < 4; np++) {
                uint32_t b[4];
                int r = sb * 64 + np * 16 + (lane & 7) + (lane >> 4) * 8;
                int ch = (lane >> 3) & 1;
                int pc = ch ^ ((r >> 2) & 1);
                ldsm_x4(b[0], b[1], b[2], b[3], smem_u32(kk + r * 16 + pc * 8));
#pragma unroll
                for (int mt = 0; mt < 2; mt++) {
#pragma unroll
                    for (int e = 0; e < 4; e++) s[mt][np * 2][e] = s[mt][np * 2 + 1][e] = 0.f;
                    mma16816(s[mt][np * 2], qf[mt], b[0], b[1]);
                    mma16816(s[mt][np * 2 + 1], qf[mt], b[2], b[3]);
                }
            }
            uint32_t pf[2][4][4];
#pragma unroll
            for (int mt = 0; mt < 2; mt++) {
                float m0 = mx[mt][0], m1 = mx[mt][1];
#pragma unroll
                for (int n = 0; n < 8; n++) {
                    m0 = fmaxf(m0, fmaxf(s[mt][n][0], s[mt][n][1]));
                    m1 = fmaxf(m1, fmaxf(s[mt][n][2], s[mt][n][3]));
                }
                m0 = fmaxf(m0, __shfl_xor_sync(~0u, m0, 1)); m0 = fmaxf(m0, __shfl_xor_sync(~0u, m0, 2));
                m1 = fmaxf(m1, __shfl_xor_sync(~0u, m1, 1)); m1 = fmaxf(m1, __shfl_xor_sync(~0u, m1, 2));
                float a0 = exp2f((mx[mt][0] - m0) * SC), a1 = exp2f((mx[mt][1] - m1) * SC);
                mx[mt][0] = m0; mx[mt][1] = m1;
                float ms0 = m0 * SC, ms1 = m1 * SC;
                float r0 = 0.f, r1 = 0.f;
#pragma unroll
                for (int n = 0; n < 8; n++) {
                    float p0 = exp2f(fmaf(s[mt][n][0], SC, -ms0)), p1 = exp2f(fmaf(s[mt][n][1], SC, -ms0));
                    float p2 = exp2f(fmaf(s[mt][n][2], SC, -ms1)), p3 = exp2f(fmaf(s[mt][n][3], SC, -ms1));
                    r0 += p0 + p1; r1 += p2 + p3;
                    pf[mt][n >> 1][(n & 1) * 2] = pack_bf16(p0, p1);
                    pf[mt][n >> 1][(n & 1) * 2 + 1] = pack_bf16(p2, p3);
                }
                sm_[mt][0] = sm_[mt][0] * a0 + r0; sm_[mt][1] = sm_[mt][1] * a1 + r1;
#pragma unroll
                for (int n = 0; n < 2; n++) { o[mt][n][0] *= a0; o[mt][n][1] *= a0; o[mt][n][2] *= a1; o[mt][n][3] *= a1; }
            }
#pragma unroll
            for (int ks = 0; ks < 4; ks++) {
                uint32_t b[4];
                int r = sb * 64 + ks * 16 + (lane & 7) + ((lane >> 3) & 1) * 8;
                int ch = lane >> 4;
                int pc = ch ^ ((r >> 2) & 1);
                ldsm_x4_t(b[0], b[1], b[2], b[3], smem_u32(vv + r * 16 + pc * 8));
#pragma unroll
                for (int mt = 0; mt < 2; mt++) {
                    mma16816(o[mt][0], pf[mt][ks], b[0], b[1]);
                    mma16816(o[mt][1], pf[mt][ks], b[2], b[3]);
                }
            }
        }
    }
#pragma unroll
    for (int mt = 0; mt < 2; mt++) {
        float l0 = sm_[mt][0], l1 = sm_[mt][1];
        l0 += __shfl_xor_sync(~0u, l0, 1); l0 += __shfl_xor_sync(~0u, l0, 2);
        l1 += __shfl_xor_sync(~0u, l1, 1); l1 += __shfl_xor_sync(~0u, l1, 2);
        float i0 = 1.f / l0, i1 = 1.f / l1;
#pragma unroll
        for (int n = 0; n < 2; n++) {
            bf16* dst = g_oa + (size_t)(q0 + mt * 16 + (lane >> 2)) * 512 + h * 16 + n * 8 + (lane & 3) * 2;
            *reinterpret_cast<uint32_t*>(dst) = pack_bf16(o[mt][n][0] * i0, o[mt][n][1] * i0);
            *reinterpret_cast<uint32_t*>(dst + 8 * 512) = pack_bf16(o[mt][n][2] * i1, o[mt][n][3] * i1);
        }
    }
}

constexpr int R_KV = 0;
constexpr int R_KV_BUF = 48 * 256;
constexpr int R_QM = R_KV + 4 * R_KV_BUF;
constexpr int R_QX = R_QM + 2048;
constexpr int R_PART = R_QX + 4096;
constexpr int R_S = R_PART + 32768;
constexpr int R_P = R_S + 8 * 48 * 4;
constexpr int R_O = R_P + 8 * 56 * 2;
constexpr int R_RED = R_O + 8 * 136 * 2;
constexpr int R_BAR = R_RED + 1024;
constexpr int R_SMEM = R_BAR + 16;

__device__ __forceinline__ void rec_attention(unsigned char* sm, uint32_t q_addr, uint32_t k_addr, uint32_t v_addr,
                                              int lim, int inc, int tid) {
    const int lane = tid & 31, warp = tid >> 5;
    float* Ssm = reinterpret_cast<float*>(sm + R_S);
    bf16* Psm = reinterpret_cast<bf16*>(sm + R_P);
    bf16* Osm = reinterpret_cast<bf16*>(sm + R_O);
    const float scale = 0.08838834764831845f;
    if (warp < 3) {
        float c0[4] = {0, 0, 0, 0}, c1[4] = {0, 0, 0, 0};
        const int row = warp * 16 + (lane & 7) + ((lane >> 3) & 1) * 8;
#pragma unroll
        for (int i = 0; i < 4; i++) {
            uint32_t qb[4], a[4];
            {
                int r = lane & 7, ch = 4 * i + (lane >> 3);
                ldsm_x4(qb[0], qb[1], qb[2], qb[3], q_addr + r * 256 + ((ch ^ r) << 4));
            }
            {
                int ch = 4 * i + (lane >> 4);
                ldsm_x4(a[0], a[1], a[2], a[3], k_addr + row * 256 + ((ch ^ (row & 7)) << 4));
                mma16816(c0, a, qb[0], qb[1]);
                ch += 2;
                ldsm_x4(a[0], a[1], a[2], a[3], k_addr + row * 256 + ((ch ^ (row & 7)) << 4));
                mma16816(c1, a, qb[2], qb[3]);
            }
        }
        const int key = warp * 16 + (lane >> 2), q = (lane & 3) * 2;
        Ssm[q * 48 + key] = bf16r(bf16r(c0[0] + c1[0]) * scale);
        Ssm[(q + 1) * 48 + key] = bf16r(bf16r(c0[1] + c1[1]) * scale);
        Ssm[q * 48 + key + 8] = bf16r(bf16r(c0[2] + c1[2]) * scale);
        Ssm[(q + 1) * 48 + key + 8] = bf16r(bf16r(c0[3] + c1[3]) * scale);
    }
    __syncthreads();
    if (warp < 2) {
        const int r = warp * 4 + (lane >> 3), sub = lane & 7;
        const int kmax = lim + r * inc;
        float v[5];
        float m = -INFINITY;
#pragma unroll
        for (int i = 0; i < 5; i++) {
            int key = sub + 8 * i;
            v[i] = (key <= kmax) ? Ssm[r * 48 + key] : -INFINITY;
            m = fmaxf(m, v[i]);
        }
        m = fmaxf(m, __shfl_xor_sync(~0u, m, 1));
        m = fmaxf(m, __shfl_xor_sync(~0u, m, 2));
        m = fmaxf(m, __shfl_xor_sync(~0u, m, 4));
        float sum = 0.f;
#pragma unroll
        for (int i = 0; i < 5; i++) { v[i] = __expf(v[i] - m); sum += v[i]; }
        sum += __shfl_xor_sync(~0u, sum, 1);
        sum += __shfl_xor_sync(~0u, sum, 2);
        sum += __shfl_xor_sync(~0u, sum, 4);
        const float inv = 1.f / sum;
#pragma unroll
        for (int i = 0; i < 5; i++) Psm[r * 56 + sub + 8 * i] = __float2bfloat16_rn(v[i] * inv);
    }
    __syncthreads();
    {
        uint32_t pb[6];
        const uint32_t p_addr = smem_u32(Psm);
        ldsm_x4(pb[0], pb[1], pb[2], pb[3], p_addr + (lane & 7) * 112 + (lane >> 3) * 16);
        ldsm_x2(pb[4], pb[5], p_addr + (lane & 7) * 112 + (4 + ((lane >> 3) & 1)) * 16);
        float c[4] = {0, 0, 0, 0};
#pragma unroll
        for (int ks = 0; ks < 3; ks++) {
            uint32_t a[4];
            int row = ks * 16 + (lane & 7) + (lane >> 4) * 8;
            int ch = 2 * warp + ((lane >> 3) & 1);
            ldsm_x4_t(a[0], a[1], a[2], a[3], v_addr + row * 256 + ((ch ^ (row & 7)) << 4));
            mma16816(c, a, pb[ks * 2], pb[ks * 2 + 1]);
        }
        const int d = warp * 16 + (lane >> 2), q = (lane & 3) * 2;
        Osm[q * 136 + d] = __float2bfloat16_rn(c[0]);
        Osm[(q + 1) * 136 + d] = __float2bfloat16_rn(c[1]);
        Osm[q * 136 + d + 8] = __float2bfloat16_rn(c[2]);
        Osm[(q + 1) * 136 + d + 8] = __float2bfloat16_rn(c[3]);
    }
    __syncthreads();
}

__global__ void __launch_bounds__(256, 1)
rec_kernel(const bf16* __restrict__ mem0, const bf16* __restrict__ Wq, const bf16* __restrict__ Wk,
           const bf16* __restrict__ Wv, const bf16* __restrict__ Wo) {
    extern __shared__ __align__(1024) unsigned char sm[];
    const int tid = threadIdx.x, lane = tid & 31, warp = tid >> 5;
    const int cta = blockIdx.x, h = cta >> 2, j = cta & 3;
    const uint32_t sbase = smem_u32(sm);
    const unsigned E = *(volatile unsigned*)&g_epoch;

    for (int i = tid; i < 4 * 128; i += 256) {
        int b = i >> 7, c = i & 127;
        *reinterpret_cast<uint4*>(sm + R_KV + b * R_KV_BUF + 40 * 256 + c * 16) = make_uint4(0, 0, 0, 0);
    }
    if (tid < 8 * 56 / 2) reinterpret_cast<uint32_t*>(sm + R_P)[tid] = 0;

    uint32_t wq[6][4][4];
    uint32_t wo[8][4];
    {
        unsigned char* stg = sm + R_PART + warp * 4096;
        const uint32_t stg_a = smem_u32(stg);
#pragma unroll
        for (int mat = 0; mat < 3; mat++) {
            const bf16* W = (mat == 0 ? Wq : (mat == 1 ? Wk : Wv)) + (size_t)(warp * 64) * 4096 + h * 128 + j * 32;
#pragma unroll
            for (int i = 0; i < 8; i++) {
                int c = lane + i * 32, r = c >> 2, ch = c & 3;
                *reinterpret_cast<uint4*>(stg + r * 64 + ch * 16) = __ldg(reinterpret_cast<const uint4*>(W + (size_t)r * 4096 + ch * 8));
            }
            __syncwarp();
#pragma unroll
            for (int mh = 0; mh < 2; mh++)
#pragma unroll
                for (int kt = 0; kt < 4; kt++) {
                    int r = kt * 16 + (lane & 7) + (lane >> 4) * 8;
                    int ch = mh * 2 + ((lane >> 3) & 1);
                    uint32_t* f = wq[mat * 2 + mh][kt];
                    ldsm_x4_t(f[0], f[1], f[2], f[3], stg_a + r * 64 + ch * 16);
                }
            __syncwarp();
        }
        {
            const bf16* W = Wo + (size_t)(h * 128) * 512 + j * 128 + warp * 16;
#pragma unroll
            for (int i = 0; i < 8; i++) {
                int c = lane + i * 32, r = c >> 1, ch = c & 1;
                *reinterpret_cast<uint4*>(stg + r * 32 + ch * 16) = __ldg(reinterpret_cast<const uint4*>(W + (size_t)r * 512 + ch * 8));
            }
            __syncwarp();
#pragma unroll
            for (int kt = 0; kt < 8; kt++) {
                int r = kt * 16 + (lane & 7) + (lane >> 4) * 8;
                int ch = (lane >> 3) & 1;
                ldsm_x4_t(wo[kt][0], wo[kt][1], wo[kt][2], wo[kt][3], stg_a + r * 32 + ch * 16);
            }
            __syncwarp();
        }
    }

    auto prefetch = [&](int s) {
        if ((s & 3) == 0) {
            if (tid < 3) {
                const unsigned* f = &g_pflag[(tid * 16 + (s >> 2)) * 32 + h];
                int it = 0;
                while (ld_acquire_u32(f) != E + 1 && it < SPIN_LIMIT) it++;
            }
            __syncthreads();
        }
        const int par = s & 1;
        const bf16* qsrc = g_qkvx + (((size_t)0 * 64 + s) * 32 + h) * 4096 + j * 8 * 128;
        const bf16* ksrc = g_qkvx + (((size_t)1 * 64 + s) * 32 + h) * 4096;
        const bf16* vsrc = g_qkvx + (((size_t)2 * 64 + s) * 32 + h) * 4096;
        const uint32_t kd = sbase + R_KV + (par * 2) * R_KV_BUF + 8 * 256;
        const uint32_t vd = kd + R_KV_BUF;
#pragma unroll
        for (int i = 0; i < 2; i++) {
            int c = tid + i * 256;
            cp_async16(kd + c * 16, ksrc + c * 8);
            cp_async16(vd + c * 16, vsrc + c * 8);
        }
        if (tid < 128) cp_async16(sbase + R_QX + par * 2048 + tid * 16, qsrc + tid * 8);
        cp_async_commit();
    };

    __syncthreads();
    prefetch(0);

    for (int s = 0; s < 64; s++) {
        const int par = s & 1;
        const uint32_t k_addr = sbase + R_KV + (par * 2) * R_KV_BUF;
        const uint32_t v_addr = k_addr + R_KV_BUF;

        uint32_t mb[4][2];
        if (s == 0) {
#pragma unroll
            for (int kt = 0; kt < 4; kt++) {
                const bf16* p = mem0 + (lane >> 2) * 512 + (warp * 4 + kt) * 16 + (lane & 3) * 2;
                mb[kt][0] = *reinterpret_cast<const uint32_t*>(p);
                mb[kt][1] = *reinterpret_cast<const uint32_t*>(p + 8);
            }
        } else {
            const unsigned tag = E * 64 + s;
            const uint4* p = g_memll + warp * 128 + lane;
            uint4 a[4];
            int it = 0;
            bool bad;
            do {
                bad = false;
#pragma unroll
                for (int kt = 0; kt < 4; kt++) a[kt] = ld_relaxed_v4(p + kt * 32);
#pragma unroll
                for (int kt = 0; kt < 4; kt++) bad |= (a[kt].y != tag) | (a[kt].w != tag);
                it++;
            } while (bad && it < SPIN_LIMIT);
#pragma unroll
            for (int kt = 0; kt < 4; kt++) { mb[kt][0] = a[kt].x; mb[kt][1] = a[kt].z; }
        }

        {
            float4* part = reinterpret_cast<float4*>(sm + R_PART) + warp * 192 + lane;
#pragma unroll
            for (int mt = 0; mt < 6; mt++) {
                float c[4] = {0, 0, 0, 0};
#pragma unroll
                for (int kt = 0; kt < 4; kt++) mma16816(c, wq[mt][kt], mb[kt][0], mb[kt][1]);
                part[mt * 32] = make_float4(c[0], c[1], c[2], c[3]);
            }
        }
        __syncthreads();
        if (tid < 192) {
            const float4* part = reinterpret_cast<const float4*>(sm + R_PART) + tid;
            float4 a = part[0];
#pragma unroll
            for (int w = 1; w < 8; w++) {
                float4 b = part[w * 192];
                a.x += b.x; a.y += b.y; a.z += b.z; a.w += b.w;
            }
            const int mt = warp;
            const bool odd = (lane >> 2) & 1;
            float s0 = odd ? a.x : a.y, s1 = odd ? a.z : a.w;
            float r0 = __shfl_xor_sync(~0u, s0, 4), r1 = __shfl_xor_sync(~0u, s1, 4);
            uint32_t lo = odd ? pack_bf16(r0, a.y) : pack_bf16(a.x, r0);
            uint32_t hi = odd ? pack_bf16(r1, a.w) : pack_bf16(a.z, r1);
            const unsigned xtag = E * 64 + s + 1;
            st_relaxed_v4(g_xch + cta * 192 + tid, lo, xtag, hi, xtag);
            const int row = (lane & 3) * 2 + (odd ? 1 : 0);
            const int dl = (mt & 1) * 16 + ((lane >> 2) & ~1);
            const int mat = mt >> 1;
            unsigned char* base = sm + ((mat == 0) ? R_QM : (R_KV + (par * 2 + mat - 1) * R_KV_BUF)) + row * 256;
            auto put = [&](int jj, uint32_t vlo, uint32_t vhi) {
                const int d = jj * 32 + dl;
                *reinterpret_cast<uint32_t*>(base + (((d >> 3) ^ row) << 4) + (d & 7) * 2) = vlo;
                *reinterpret_cast<uint32_t*>(base + ((((d + 8) >> 3) ^ row) << 4) + (d & 7) * 2) = vhi;
            };
            put(j, lo, hi);
            const uint4* px = g_xch + (h * 4) * 192 + tid;
            uint4 x1, x2, x3;
            int it = 0;
            do {
                x1 = ld_relaxed_v4(px + ((j + 1) & 3) * 192);
                x2 = ld_relaxed_v4(px + ((j + 2) & 3) * 192);
                x3 = ld_relaxed_v4(px + ((j + 3) & 3) * 192);
                it++;
            } while (((x1.y != xtag) | (x1.w != xtag) | (x2.y != xtag) | (x2.w != xtag) | (x3.y != xtag) | (x3.w != xtag)) && it < SPIN_LIMIT);
            put((j + 1) & 3, x1.x, x1.z);
            put((j + 2) & 3, x2.x, x2.z);
            put((j + 3) & 3, x3.x, x3.z);
        }
        cp_async_wait<0>();
        __syncthreads();

        if (s < 63) {
            rec_attention(sm, sbase + R_QM, k_addr, v_addr, 39, 0, tid);
            {
                const uint32_t o_addr = sbase + R_O;
                float c0[4] = {0, 0, 0, 0}, c1[4] = {0, 0, 0, 0};
#pragma unroll
                for (int i = 0; i < 4; i++) {
                    uint32_t b[4];
                    ldsm_x4(b[0], b[1], b[2], b[3], o_addr + (lane & 7) * 272 + (4 * i + (lane >> 3)) * 16);
                    mma16816(c0, wo[2 * i], b[0], b[1]);
                    mma16816(c1, wo[2 * i + 1], b[2], b[3]);
                }
                const unsigned tag = E * 64 + s + 1;
                const int T = 8 * j + warp;
                const int r = 4 * T + (lane & 3);
                uint4* dst = g_part + ((size_t)r * 32 + h) * 16 + (lane >> 2) * 2;
                st_relaxed_v4(dst, __float_as_uint(c0[0] + c1[0]), tag, __float_as_uint(c0[1] + c1[1]), tag);
                st_relaxed_v4(dst + 1, __float_as_uint(c0[2] + c1[2]), tag, __float_as_uint(c0[3] + c1[3]), tag);
            }
            __syncthreads();
        }

        rec_attention(sm, sbase + R_QX + par * 2048, k_addr, v_addr, 8 + 8 * j, 1, tid);
        if (tid < 128) {
            const int r = tid >> 4, c = tid & 15;
            uint4 v = *reinterpret_cast<const uint4*>(sm + R_O + r * 272 + c * 16);
            *reinterpret_cast<uint4*>(g_ox + (size_t)(s * 32 + j * 8 + r) * 4096 + h * 128 + c * 8) = v;
        }

        if (s < 63) {
            const unsigned tag = E * 64 + s + 1;
            const uint4* p = g_part + (size_t)cta * 512 + tid;
            uint4 a, b;
            int it = 0;
            do {
                a = ld_relaxed_v4(p);
                b = ld_relaxed_v4(p + 256);
                it++;
            } while (((a.y != tag) | (a.w != tag) | (b.y != tag) | (b.w != tag)) && it < SPIN_LIMIT);
            float x0 = __uint_as_float(a.x) + __uint_as_float(b.x), x1 = __uint_as_float(a.z) + __uint_as_float(b.z);
            x0 += __shfl_xor_sync(~0u, x0, 16);
            x1 += __shfl_xor_sync(~0u, x1, 16);
            float* red = reinterpret_cast<float*>(sm + R_RED);
            if (lane < 16) { red[warp * 32 + lane * 2] = x0; red[warp * 32 + lane * 2 + 1] = x1; }
            __syncthreads();
            if (warp == 0) {
                float y = 0.f;
#pragma unroll
                for (int w = 0; w < 8; w++) y += red[w * 32 + lane];
                const int i = lane & 7, which = i >> 2, c = 2 * (i & 3);
                float v0 = __shfl_sync(~0u, y, (2 * c) * 2 + which);
                float v1 = __shfl_sync(~0u, y, (2 * (c + 1)) * 2 + which);
                float v2 = __shfl_sync(~0u, y, (2 * c + 1) * 2 + which);
                float v3 = __shfl_sync(~0u, y, (2 * (c + 1) + 1) * 2 + which);
                if (lane < 8) st_relaxed_v4(g_memll + cta * 8 + lane, pack_bf16(v0, v1), tag, pack_bf16(v2, v3), tag);
            }
            prefetch(s + 1);
        }
    }
}

extern "C" void kernel_launch(void* const* d_in, const int* in_sizes, int n_in, void* d_out, int out_size) {
    const bf16* A_x = (const bf16*)d_in[0];
    const bf16* A_wq = (const bf16*)d_in[1];
    const bf16* A_wk = (const bf16*)d_in[2];
    const bf16* A_wv = (const bf16*)d_in[3];
    const bf16* A_wo = (const bf16*)d_in[4];
    const bf16* B_x = (const bf16*)d_in[5];
    const bf16* B_mem0 = (const bf16*)d_in[6];
    const bf16* B_Wq = (const bf16*)d_in[7];
    const bf16* B_Wk = (const bf16*)d_in[8];
    const bf16* B_Wv = (const bf16*)d_in[9];
    const bf16* B_Wo = (const bf16*)d_in[10];
    bf16* out = (bf16*)d_out;

    static bool init = false;
    static cudaStream_t s1, s2;
    static cudaEvent_t e0, e1, e2;
    static bf16 *p_ox, *p_qa, *p_oa;
    if (!init) {
        cudaStreamCreateWithFlags(&s1, cudaStreamNonBlocking);
        cudaStreamCreateWithFlags(&s2, cudaStreamNonBlocking);
        cudaEventCreateWithFlags(&e0, cudaEventDisableTiming);
        cudaEventCreateWithFlags(&e1, cudaEventDisableTiming);
        cudaEventCreateWithFlags(&e2, cudaEventDisableTiming);
        cudaFuncSetAttribute(gemm_kernel<0>, cudaFuncAttributeMaxDynamicSharedMemorySize, G_SMEM);
        cudaFuncSetAttribute(gemm_kernel<1>, cudaFuncAttributeMaxDynamicSharedMemorySize, G_SMEM);
        cudaFuncSetAttribute(kv_a_kernel, cudaFuncAttributeMaxDynamicSharedMemorySize, KV_SMEM);
        cudaFuncSetAttribute(rec_kernel, cudaFuncAttributeMaxDynamicSharedMemorySize, R_SMEM);
        cudaGetSymbolAddress((void**)&p_ox, g_ox);
        cudaGetSymbolAddress((void**)&p_qa, g_qa);
        cudaGetSymbolAddress((void**)&p_oa, g_oa);
        init = true;
    }
    cudaStream_t s0 = cudaStreamPerThread;

    cudaEventRecord(e0, s0);
    cudaStreamWaitEvent(s1, e0, 0);
    cudaStreamWaitEvent(s2, e0, 0);

    rec_kernel<<<128, 256, R_SMEM, s0>>>(B_mem0, B_Wq, B_Wk, B_Wv, B_Wo);

    {
        GemmArgs g{};
        g.A = B_x; g.lda = 512; g.B0 = B_Wq; g.B1 = B_Wk; g.B2 = B_Wv; g.ldb = 4096; g.C = nullptr; g.ldc = 0; g.K = 512; g.finalize = 0;
        gemm_kernel<1><<<16 * 96, 256, G_SMEM, s1>>>(g);
    }
    {
        kv_a_kernel<<<64, 256, KV_SMEM, s2>>>(A_x, A_wk, A_wv);
        GemmArgs g{};
        g.A = A_x; g.lda = 512; g.B0 = A_wq; g.ldb = 512; g.C = p_qa; g.ldc = 512; g.K = 512; g.finalize = 0;
        gemm_kernel<0><<<dim3(4, 16), 256, G_SMEM, s2>>>(g);
        attn_a_kernel<<<256, 256, 0, s2>>>();
        GemmArgs g2{};
        g2.A = p_oa; g2.lda = 512; g2.B0 = A_wo; g2.ldb = 512; g2.C = out; g2.ldc = 1024; g2.K = 512; g2.finalize = 0;
        gemm_kernel<0><<<dim3(4, 16), 256, G_SMEM, s2>>>(g2);
    }
    cudaEventRecord(e1, s1);
    cudaEventRecord(e2, s2);
    cudaStreamWaitEvent(s0, e1, 0);
    cudaStreamWaitEvent(s0, e2, 0);
    {
        GemmArgs g{};
        g.A = p_ox; g.lda = 4096; g.B0 = B_Wo; g.ldb = 512; g.C = out + 512; g.ldc = 1024; g.K = 4096; g.finalize = 1;
        gemm_kernel<0><<<dim3(4, 16), 256, G_SMEM, s0>>>(g);
    }
}
```

```cpp
#include <cuda_runtime.h>
#include <cuda.h>
#include <cuda_bf16.h>
#include <stdint.h>
#include <type_traits>

typedef __nv_bfloat16 bf16;
constexpr int SPIN_LIMIT = 1 << 18;

__device__ __align__(1024) bf16 g_qkvx[3 * 64 * 32 * 32 * 128];
__device__ __align__(1024) bf16 g_ox[2048 * 4096];
__device__ __align__(1024) uint4 g_acc[4 * 2048];
__device__ __align__(1024) uint4 g_fin[16 * 11 * 32];
__device__ unsigned g_pflag[3 * 16 * 32];
__device__ unsigned g_oxcnt[17];
constexpr int NS1 = 8;
constexpr int OG_Q1 = 48 - NS1;
__device__ __align__(1024) float g_skp[288 * 128 * 128];
__device__ unsigned g_skc[68];
__device__ unsigned g_done;
__device__ unsigned g_epoch;
__device__ __align__(1024) bf16 g_qa[2048 * 512];
__device__ __align__(1024) bf16 g_ka[2048 * 16];
__device__ __align__(1024) bf16 g_va[2048 * 16];
__device__ __align__(1024) bf16 g_oa[2048 * 512];

#define TL_BEG(k)
#define TL_END(k)
#define PROF_DECL
#define PROF(i)
#define PROF_END
__device__ __forceinline__ uint32_t smem_u32(const void* p) { return (uint32_t)__cvta_generic_to_shared(p); }

__device__ __forceinline__ void ldsm_x4(uint32_t& r0, uint32_t& r1, uint32_t& r2, uint32_t& r3, uint32_t a) {
    asm volatile("ldmatrix.sync.aligned.m8n8.x4.shared.b16 {%0,%1,%2,%3}, [%4];"
                 : "=r"(r0), "=r"(r1), "=r"(r2), "=r"(r3) : "r"(a) : "memory");
}
__device__ __forceinline__ void ldsm_x4_t(uint32_t& r0, uint32_t& r1, uint32_t& r2, uint32_t& r3, uint32_t a) {
    asm volatile("ldmatrix.sync.aligned.m8n8.x4.trans.shared.b16 {%0,%1,%2,%3}, [%4];"
                 : "=r"(r0), "=r"(r1), "=r"(r2), "=r"(r3) : "r"(a) : "memory");
}
__device__ __forceinline__ void ldsm_x2(uint32_t& r0, uint32_t& r1, uint32_t a) {
    asm volatile("ldmatrix.sync.aligned.m8n8.x2.shared.b16 {%0,%1}, [%2];" : "=r"(r0), "=r"(r1) : "r"(a) : "memory");
}
__device__ __forceinline__ void ldsm_x2_t(uint32_t& r0, uint32_t& r1, uint32_t a) {
    asm volatile("ldmatrix.sync.aligned.m8n8.x2.trans.shared.b16 {%0,%1}, [%2];" : "=r"(r0), "=r"(r1) : "r"(a) : "memory");
}
__device__ __forceinline__ float4 lds128(uint32_t a) {
    float4 v;
    asm volatile("ld.shared.v4.f32 {%0,%1,%2,%3}, [%4];" : "=f"(v.x), "=f"(v.y), "=f"(v.z), "=f"(v.w) : "r"(a) : "memory");
    return v;
}
__device__ __forceinline__ uint32_t lds32(uint32_t a) {
    uint32_t v;
    asm volatile("ld.shared.u32 %0, [%1];" : "=r"(v) : "r"(a) : "memory");
    return v;
}
__device__ __forceinline__ void sts32(uint32_t a, uint32_t v) { asm volatile("st.shared.u32 [%0], %1;" ::"r"(a), "r"(v) : "memory"); }
__device__ __forceinline__ float bf_lo(uint32_t v) { return __uint_as_float(v << 16); }
__device__ __forceinline__ float bf_hi(uint32_t v) { return __uint_as_float(v & 0xffff0000u); }
__device__ __forceinline__ void mma16816(float* c, const uint32_t* a, uint32_t b0, uint32_t b1) {
    asm volatile("mma.sync.aligned.m16n8k16.row.col.f32.bf16.bf16.f32 {%0,%1,%2,%3}, {%4,%5,%6,%7}, {%8,%9}, {%0,%1,%2,%3};"
                 : "+f"(c[0]), "+f"(c[1]), "+f"(c[2]), "+f"(c[3])
                 : "r"(a[0]), "r"(a[1]), "r"(a[2]), "r"(a[3]), "r"(b0), "r"(b1));
}
__device__ __forceinline__ void cp_async16(uint32_t dst, const void* src) {
    asm volatile("cp.async.cg.shared.global [%0], [%1], 16;" ::"r"(dst), "l"(src) : "memory");
}
__device__ __forceinline__ void cp_async_commit() { asm volatile("cp.async.commit_group;" ::: "memory"); }
template <int N> __device__ __forceinline__ void cp_async_wait() { asm volatile("cp.async.wait_group %0;" ::"n"(N) : "memory"); }

__device__ __forceinline__ uint4 ld_relaxed_v4(const uint4* p) {
    uint4 v;
    asm volatile("ld.relaxed.gpu.global.v4.u32 {%0,%1,%2,%3}, [%4];" : "=r"(v.x), "=r"(v.y), "=r"(v.z), "=r"(v.w) : "l"(p) : "memory");
    return v;
}
__device__ __forceinline__ void st_relaxed_v4(uint4* p, uint32_t x, uint32_t y, uint32_t z, uint32_t w) {
    asm volatile("st.relaxed.gpu.global.v4.u32 [%0], {%1,%2,%3,%4};" ::"l"(p), "r"(x), "r"(y), "r"(z), "r"(w) : "memory");
}
__device__ __forceinline__ void red_add_v4(uint4* p, float x, float y, float z, float w) {
    asm volatile("red.relaxed.gpu.global.add.v4.f32 [%0], {%1,%2,%3,%4};" ::"l"(p), "f"(x), "f"(y), "f"(z), "f"(w) : "memory");
}
__device__ __forceinline__ unsigned ld_relaxed_u32(const unsigned* p) {
    unsigned v;
    asm volatile("ld.relaxed.gpu.global.u32 %0, [%1];" : "=r"(v) : "l"(p) : "memory");
    return v;
}
__device__ __forceinline__ unsigned ld_acquire_u32(const unsigned* p) {
    unsigned v;
    asm volatile("ld.acquire.gpu.global.u32 %0, [%1];" : "=r"(v) : "l"(p) : "memory");
    return v;
}
__device__ __forceinline__ void st_release_u32(unsigned* p, unsigned v) {
    asm volatile("st.release.gpu.global.u32 [%0], %1;" ::"l"(p), "r"(v) : "memory");
}
__device__ __forceinline__ uint32_t mapa(uint32_t a, uint32_t r) {
    uint32_t o;
    asm volatile("mapa.shared::cluster.u32 %0, %1, %2;" : "=r"(o) : "r"(a), "r"(r));
    return o;
}
__device__ __forceinline__ void st_cluster32(uint32_t a, uint32_t v) { asm volatile("st.shared::cluster.u32 [%0], %1;" ::"r"(a), "r"(v) : "memory"); }
__device__ __forceinline__ void st_async_b32(uint32_t dst, uint32_t v, uint32_t mbar) {
    asm volatile("st.async.weak.shared::cluster.mbarrier::complete_tx::bytes.b32 [%0], %1, [%2];" ::"r"(dst), "r"(v), "r"(mbar) : "memory");
}
__device__ __forceinline__ void st_async_v4(uint32_t dst, uint32_t a, uint32_t b, uint32_t c, uint32_t d, uint32_t mbar) {
    asm volatile("st.async.weak.shared::cluster.mbarrier::complete_tx::bytes.v4.b32 [%0], {%1,%2,%3,%4}, [%5];"
                 ::"r"(dst), "r"(a), "r"(b), "r"(c), "r"(d), "r"(mbar) : "memory");
}
__device__ __forceinline__ void bulk_g2s(uint32_t dst, const void* src, uint32_t bytes, uint32_t mbar) {
    asm volatile("cp.async.bulk.shared::cluster.global.mbarrier::complete_tx::bytes [%0], [%1], %2, [%3];"
                 ::"r"(dst), "l"(src), "r"(bytes), "r"(mbar) : "memory");
}
__device__ __forceinline__ void mbar_wait(uint32_t a, uint32_t par) {
    uint32_t ok = 0;
    int it = 0;
    while (!ok && it < SPIN_LIMIT) {
        asm volatile("{.reg .pred p; mbarrier.try_wait.parity.shared::cta.b64 p, [%1], %2; selp.u32 %0,1,0,p;}"
                     : "=r"(ok) : "r"(a), "r"(par) : "memory");
        it++;
    }
}
__device__ __forceinline__ uint32_t pack_bf16(float lo, float hi) {
    __nv_bfloat162 v = __floats2bfloat162_rn(lo, hi);
    return *reinterpret_cast<uint32_t*>(&v);
}
__device__ __forceinline__ float ex2f(float x) { float y; asm("ex2.approx.ftz.f32 %0, %1;" : "=f"(y) : "f"(x)); return y; }
__device__ __forceinline__ float rcpf(float x) { float y; asm("rcp.approx.ftz.f32 %0, %1;" : "=f"(y) : "f"(x)); return y; }
__device__ __forceinline__ float bf16r(float x) { return __bfloat162float(__float2bfloat16_rn(x)); }

constexpr int W_STAGES = 3;
constexpr int W_STAGE_BYTES = 32768;
constexpr int W_SMEM = W_STAGES * W_STAGE_BYTES + 1024 + 64;

__device__ __forceinline__ void mbar_init(uint32_t a, uint32_t cnt) { asm volatile("mbarrier.init.shared::cta.b64 [%0], %1;" ::"r"(a), "r"(cnt) : "memory"); }
__device__ __forceinline__ void mbar_expect(uint32_t a, uint32_t bytes) {
    asm volatile("mbarrier.arrive.expect_tx.shared::cta.b64 _, [%0], %1;" ::"r"(a), "r"(bytes) : "memory");
}
__device__ __forceinline__ void tma2d(uint32_t dst, const CUtensorMap* tm, int c0, int c1, uint32_t mbar) {
    asm volatile("cp.async.bulk.tensor.2d.shared::cluster.global.mbarrier::complete_tx::bytes [%0], [%1, {%3, %4}], [%2];"
                 ::"r"(dst), "l"(reinterpret_cast<uint64_t>(tm)), "r"(mbar), "r"(c0), "r"(c1) : "memory");
}
__device__ __forceinline__ void wgmma128(float* d, uint64_t da, uint64_t db, int acc) {
    asm volatile(
        "{\n.reg .pred p;\nsetp.ne.b32 p, %66, 0;\n"
        "wgmma.mma_async.sync.aligned.m64n128k16.f32.bf16.bf16 "
        "{%0,%1,%2,%3,%4,%5,%6,%7,%8,%9,%10,%11,%12,%13,%14,%15,%16,%17,%18,%19,%20,%21,%22,%23,%24,%25,%26,%27,%28,%29,%30,%31,"
        "%32,%33,%34,%35,%36,%37,%38,%39,%40,%41,%42,%43,%44,%45,%46,%47,%48,%49,%50,%51,%52,%53,%54,%55,%56,%57,%58,%59,%60,%61,%62,%63},"
        "%64, %65, p, 1, 1, 0, 1;\n}\n"
        : "+f"(d[0]), "+f"(d[1]), "+f"(d[2]), "+f"(d[3]), "+f"(d[4]), "+f"(d[5]), "+f"(d[6]), "+f"(d[7]),
          "+f"(d[8]), "+f"(d[9]), "+f"(d[10]), "+f"(d[11]), "+f"(d[12]), "+f"(d[13]), "+f"(d[14]), "+f"(d[15]),
          "+f"(d[16]), "+f"(d[17]), "+f"(d[18]), "+f"(d[19]), "+f"(d[20]), "+f"(d[21]), "+f"(d[22]), "+f"(d[23]),
          "+f"(d[24]), "+f"(d[25]), "+f"(d[26]), "+f"(d[27]), "+f"(d[28]), "+f"(d[29]), "+f"(d[30]), "+f"(d[31]),
          "+f"(d[32]), "+f"(d[33]), "+f"(d[34]), "+f"(d[35]), "+f"(d[36]), "+f"(d[37]), "+f"(d[38]), "+f"(d[39]),
          "+f"(d[40]), "+f"(d[41]), "+f"(d[42]), "+f"(d[43]), "+f"(d[44]), "+f"(d[45]), "+f"(d[46]), "+f"(d[47]),
          "+f"(d[48]), "+f"(d[49]), "+f"(d[50]), "+f"(d[51]), "+f"(d[52]), "+f"(d[53]), "+f"(d[54]), "+f"(d[55]),
          "+f"(d[56]), "+f"(d[57]), "+f"(d[58]), "+f"(d[59]), "+f"(d[60]), "+f"(d[61]), "+f"(d[62]), "+f"(d[63])
        : "l"(da), "l"(db), "r"(acc));
}

template <int EPI>
__global__ void __launch_bounds__(128) gemm_wg(const __grid_constant__ CUtensorMap tmA, const __grid_constant__ CUtensorMap tmB0,
                                               const __grid_constant__ CUtensorMap tmB1, const __grid_constant__ CUtensorMap tmB2,
                                               bf16* __restrict__ C, int ldc, int nk, int ntn) {
    extern __shared__ unsigned char smem_raw[];
    const uint32_t sraw = smem_u32(smem_raw);
    const uint32_t sb = (sraw + 1023) & ~1023u;
    unsigned char* sgen = smem_raw + (sb - sraw);
    const uint32_t bars = sb + W_STAGES * W_STAGE_BYTES;
    const int tid = threadIdx.x, lane = tid & 31, warp = tid >> 5;
    int bm = blockIdx.x / ntn, bn = blockIdx.x % ntn;
    if (EPI == 0) asm volatile("griddepcontrol.launch_dependents;" ::: "memory");
    int k0 = 0, sk = -1;
    int skt = 0, nsk = 0, slot = 0, hb = 0;
    bool m64 = false;
    if (EPI == 2) {
        const int q = bm + nk;
        if (q < NS1) { bm = q; nsk = 1; }
        else if (q < 24 - NS1) { bm = (q + NS1) >> 1; sk = (q + NS1) & 1; nsk = 2; slot = (bm * 4 + bn) * 2; }
        else if (q < 56 - NS1) { bm = 12 + ((q + NS1 - 24) >> 3); sk = (q + NS1) & 7; nsk = 8; slot = 96 + ((bm - 12) * 4 + bn) * 8; }
        else { hb = 1; m64 = true; bm = 15; sk = q + NS1 - 56; nsk = 16; slot = 224 + bn * 16; }
        skt = (bm + hb) * 4 + bn; nk = 64 / nsk; k0 = nsk > 1 ? sk * nk : 0;
    }
    const int row0 = bm * 128 + hb * 64;
    const uint32_t sbytes = m64 ? 24576 : W_STAGE_BYTES, boff = m64 ? 8192 : 16384;
    const int npre = m64 ? 4 : W_STAGES;
    const bool act = hb == 0 || warp < 2;
    TL_BEG(EPI == 0 ? (ldc == 512 ? 3 : 5) : (EPI == 1 ? 1 : 6))
    const CUtensorMap* tb = &tmB0;
    int n0 = bn * 128;
    if (EPI == 1) {
        const int which = bn >> 5;
        tb = (which == 0) ? &tmB0 : (which == 1 ? &tmB1 : &tmB2);
        n0 = (bn & 31) * 128;
    }
    unsigned E = 0;
    if (EPI != 0) E = *(volatile unsigned*)&g_epoch;
    auto issue_b = [&](int kt) {
        const int st = m64 ? kt : kt % W_STAGES;
        const uint32_t a = sb + st * sbytes + boff, bar = bars + st * 8;
        mbar_expect(bar, sbytes);
        tma2d(a, tb, n0, (k0 + kt) * 64, bar);
        tma2d(a + 8192, tb, n0 + 64, (k0 + kt) * 64, bar);
    };
    auto issue_a = [&](int kt) {
        const int st = m64 ? kt : kt % W_STAGES;
        tma2d(sb + st * sbytes, m64 ? &tmB1 : &tmA, (k0 + kt) * 64, row0, bars + st * 8);
    };
    auto issue = [&](int kt) { issue_b(kt); issue_a(kt); };
    if (tid == 0) {
#pragma unroll
        for (int i = 0; i < 4; i++) mbar_init(bars + i * 8, 1);
        asm volatile("fence.mbarrier_init.release.cluster;" ::: "memory");
        asm volatile("fence.proxy.async;" ::: "memory");
        for (int i = 0; i < npre && i < nk; i++) issue_b(i);
        if (EPI == 2) {
            const unsigned target = (E + 1) * (bm == 15 ? 512u : 64u);
            const unsigned ns = bm == 15 ? 40 : 200;
            int it = 0;
            while ((int)(ld_relaxed_u32(&g_oxcnt[bm < 11 ? 10 : (bm < 14 ? 13 : bm + hb)]) - target) < 0 && it < SPIN_LIMIT * 8) { __nanosleep(ns); it++; }
            __threadfence();
            asm volatile("fence.proxy.async;" ::: "memory");
        }
        for (int i = 0; i < npre && i < nk; i++) issue_a(i);
    }
    __syncthreads();
    if (hb) { TL_BEG(8) TL_END(8) }

    float acc[2][64];
    const uint64_t dbase = (uint64_t)1 << 62 | (uint64_t)64 << 32;
    if (EPI == 2 && m64) {
        for (int kt = 0; kt < 4; kt++) {
            mbar_wait(bars + kt * 8, 0);
            const uint32_t a = sb + kt * 24576;
            asm volatile("wgmma.fence.sync.aligned;" ::: "memory");
#pragma unroll
            for (int k = 0; k < 4; k++) {
                const uint64_t db = dbase | ((uint64_t)512 << 16) | (uint64_t)(((a + 8192 + k * 2048) & 0x3FFFF) >> 4);
                const uint64_t da0 = dbase | ((uint64_t)1 << 16) | (uint64_t)(((a + k * 32) & 0x3FFFF) >> 4);
                wgmma128(acc[0], da0, db, kt | k);
            }
            asm volatile("wgmma.commit_group.sync.aligned;" ::: "memory");
        }
        nk = 0;
    }
    for (int kt = 0; kt < nk; kt++) {
        const int st = kt % W_STAGES;
        mbar_wait(bars + st * 8, (kt / W_STAGES) & 1);
        const uint32_t a = sb + st * W_STAGE_BYTES;
        asm volatile("wgmma.fence.sync.aligned;" ::: "memory");
#pragma unroll
        for (int k = 0; k < 4; k++) {
            const uint64_t db = dbase | ((uint64_t)512 << 16) | (uint64_t)(((a + 16384 + k * 2048) & 0x3FFFF) >> 4);
            const uint64_t da0 = dbase | ((uint64_t)1 << 16) | (uint64_t)(((a + k * 32) & 0x3FFFF) >> 4);
            const uint64_t da1 = dbase | ((uint64_t)1 << 16) | (uint64_t)(((a + 8192 + k * 32) & 0x3FFFF) >> 4);
            wgmma128(acc[0], da0, db, kt | k);
            wgmma128(acc[1], da1, db, kt | k);
        }
        asm volatile("wgmma.commit_group.sync.aligned;" ::: "memory");
        if (kt >= 1 && kt - 1 + W_STAGES < nk) {
            asm volatile("wgmma.wait_group.sync.aligned 1;" ::: "memory");
            __syncthreads();
            if (tid == 0) issue(kt - 1 + W_STAGES);
        }
    }
    asm volatile("wgmma.wait_group.sync.aligned 0;" ::: "memory");
    __syncthreads();

    if (hb) { TL_BEG(9) TL_END(9) }
    if (EPI == 2 && sk >= 0) {
        float4* mine = reinterpret_cast<float4*>(g_skp) + ((size_t)(slot + sk) * 32) * 128 + tid;
#pragma unroll
        for (int i = 0; i < 32; i++) {
            const float* q = &acc[i >> 4][(i & 15) * 4];
            if (i < 16 ? act : bm != 15) __stcg(mine + i * 128, make_float4(q[0], q[1], q[2], q[3]));
        }
        __threadfence();
        __syncthreads();
        if (hb) { TL_BEG(10) TL_END(10) }
        if (tid == 0) {
            const unsigned target = (E + 1) * nsk;
            atomicAdd(&g_skc[skt], 1u);
            int it = 0;
            while ((int)(ld_relaxed_u32(&g_skc[skt]) - target) < 0 && it < SPIN_LIMIT * 8) { __nanosleep(20); it++; }
            __threadfence();
        }
        __syncthreads();
        if (hb) { TL_BEG(11) TL_END(11) }
        auto reduce = [&](auto NSKc) {
            constexpr int NSK = decltype(NSKc)::value, PER = NSK == 16 ? 1 : 32 / NSK;
            const float4* all = reinterpret_cast<const float4*>(g_skp) + ((size_t)slot * 32 + sk * PER) * 128 + tid;
            float4 u[NSK][PER];
#pragma unroll
            for (int w = 0; w < NSK; w++)
#pragma unroll
                for (int i = 0; i < PER; i++) u[w][i] = __ldcg(all + (w * 32 + i) * 128);
#pragma unroll
            for (int i = 0; i < PER; i++) {
                float4 t = u[0][i];
#pragma unroll
                for (int w = 1; w < NSK; w++) { t.x += u[w][i].x; t.y += u[w][i].y; t.z += u[w][i].z; t.w += u[w][i].w; }
                const int ii = sk * PER + i;
                bf16* dst = C + (size_t)(row0 + (ii >> 4) * 64 + warp * 16 + (lane >> 2)) * ldc + n0 + (ii & 15) * 8 + (lane & 3) * 2;
                *reinterpret_cast<uint32_t*>(dst) = pack_bf16(t.x, t.y);
                *reinterpret_cast<uint32_t*>(dst + (size_t)8 * ldc) = pack_bf16(t.z, t.w);
            }
        };
        if (nsk == 2) reduce(std::integral_constant<int, 2>{});
        else if (nsk == 8) { if (bm != 15 || sk < 4) reduce(std::integral_constant<int, 8>{}); }
        else if (act) reduce(std::integral_constant<int, 16>{});
        if (tid == 0 && atomicAdd(&g_done, 1u) == 287 - 4 * NS1) { g_done = 0; __threadfence(); *(volatile unsigned*)&g_epoch = E + 1; }
        TL_END(6)
        return;
    }
#pragma unroll
    for (int hf = 0; hf < 2; hf++)
#pragma unroll
        for (int n = 0; n < 16; n++)
#pragma unroll
            for (int u = 0; u < 2; u++) {
                const int row = hf * 64 + warp * 16 + (lane >> 2) + u * 8;
                *reinterpret_cast<uint32_t*>(sgen + row * 256 + ((n ^ (row & 7)) << 4) + (lane & 3) * 4) =
                    pack_bf16(acc[hf][n * 4 + u * 2], acc[hf][n * 4 + u * 2 + 1]);
            }
    __syncthreads();
    if (EPI == 1) {
        const int which = bn >> 5, h = bn & 31;
#pragma unroll 4
        for (int i = 0; i < 16; i++) {
            const int c = tid + i * 128;
            const int seg = bm * 4 + (c >> 9);
            uint4 v = *reinterpret_cast<const uint4*>(sgen + c * 16);
            *reinterpret_cast<uint4*>(g_qkvx + (((size_t)which * 64 + seg) * 32 + h) * 4096 + (c & 511) * 8) = v;
        }
        asm volatile("fence.proxy.async;" ::: "memory");
        __threadfence();
        __syncthreads();
        if (tid == 0) st_release_u32(&g_pflag[(which * 16 + bm) * 32 + h], E + 1);
    } else {
#pragma unroll 4
        for (int i = 0; i < 16; i++) {
            const int c = tid + i * 128;
            const int row = c >> 4, ch = c & 15;
            uint4 v = *reinterpret_cast<const uint4*>(sgen + row * 256 + ((ch ^ (row & 7)) << 4));
            *reinterpret_cast<uint4*>(C + (size_t)(bm * 128 + row) * ldc + n0 + ch * 8) = v;
        }
        if (EPI == 2 && tid == 0) {
            if (atomicAdd(&g_done, 1u) == 287 - 4 * NS1) { g_done = 0; __threadfence(); *(volatile unsigned*)&g_epoch = E + 1; }
        }
    }
    TL_END(EPI == 0 ? (ldc == 512 ? 3 : 5) : (EPI == 1 ? 1 : 6))
}

constexpr int P_STAGES = 3, P_STAGE = 49152;
constexpr int P_STG = P_STAGES * P_STAGE;
constexpr int P_BARS = P_STG + 65536;
constexpr int P_SMEM = P_BARS + 128 + 1024;
constexpr int P_NT1 = 768, P_NT = 800;
__device__ unsigned g_ptile;

__device__ __forceinline__ void mbar_arrive(uint32_t a) { asm volatile("mbarrier.arrive.shared::cta.b64 _, [%0];" ::"r"(a) : "memory"); }

__global__ void __launch_bounds__(352, 1) gemm_proj(const __grid_constant__ CUtensorMap tmX, const __grid_constant__ CUtensorMap tmWq,
                                                     const __grid_constant__ CUtensorMap tmWk, const __grid_constant__ CUtensorMap tmWv,
                                                     const __grid_constant__ CUtensorMap tmAx, const __grid_constant__ CUtensorMap tmAwq,
                                                     const bf16* __restrict__ ax, const bf16* __restrict__ awk, const bf16* __restrict__ awv) {
    extern __shared__ unsigned char smem_raw[];
    const uint32_t sraw = smem_u32(smem_raw);
    const uint32_t sb = (sraw + 1023) & ~1023u;
    unsigned char* sgen = smem_raw + (sb - sraw);
    const uint32_t full = sb + P_BARS, empty = full + 32;
    volatile int* tile_id = reinterpret_cast<volatile int*>(sgen + P_BARS + 64);
    const int tid = threadIdx.x, lane = tid & 31, warp = tid >> 5;
    const unsigned E = *(volatile unsigned*)&g_epoch;
    TL_BEG(1)
    if (tid == 0) {
#pragma unroll
        for (int i = 0; i < P_STAGES; i++) { mbar_init(full + i * 8, 1); mbar_init(empty + i * 8, 8); }
        asm volatile("fence.mbarrier_init.release.cluster;" ::: "memory");
    }
    __syncthreads();
    if (warp == 8) {
        if (lane == 0) {
            const unsigned base = E * (P_NT + gridDim.x);
            int it = 0;
            for (;;) {
                const int t = (int)(atomicAdd(&g_ptile, 1u) - base);
                const CUtensorMap *ta, *tb;
                int row, n0;
                if (t < P_NT1) {
                    const int bn2 = t % 48, which = bn2 >> 4;
                    ta = &tmX; tb = (which == 0) ? &tmWq : (which == 1 ? &tmWk : &tmWv);
                    row = (t / 48) * 128; n0 = (bn2 & 15) * 256;
                } else {
                    ta = &tmAx; tb = &tmAwq;
                    row = ((t - P_NT1) >> 1) * 128; n0 = ((t - P_NT1) & 1) * 256;
                }
                bool done = false;
                for (int kt = 0; kt < 8; kt++, it++) {
                    const int st = it % P_STAGES;
                    mbar_wait(empty + st * 8, ((it / P_STAGES) & 1) ^ 1);
                    if (kt == 0) {
                        tile_id[st] = t;
                        if (t >= P_NT) { mbar_arrive(full + st * 8); done = true; break; }
                    }
                    const uint32_t a = sb + st * P_STAGE, bar = full + st * 8;
                    mbar_expect(bar, P_STAGE);
                    tma2d(a, ta, kt * 64, row, bar);
#pragma unroll
                    for (int q = 0; q < 4; q++) tma2d(a + 16384 + q * 8192, tb, n0 + q * 64, kt * 64, bar);
                }
                if (done) break;
            }
        }
    } else if (warp > 8) {
        for (int rb = blockIdx.x * 2 + (warp - 9); rb < 128; rb += gridDim.x * 2) {
            float c[4][4] = {};
            const bf16* xp = ax + (size_t)(rb * 16 + (lane >> 2)) * 512 + (lane & 3) * 2;
            const unsigned short* wp[2] = {reinterpret_cast<const unsigned short*>(awk), reinterpret_cast<const unsigned short*>(awv)};
            const int wo = (lane & 3) * 2 * 16 + (lane >> 2);
#pragma unroll 4
            for (int kt = 0; kt < 32; kt++) {
                uint32_t a[4];
                a[0] = __ldg(reinterpret_cast<const uint32_t*>(xp + kt * 16));
                a[1] = __ldg(reinterpret_cast<const uint32_t*>(xp + 8 * 512 + kt * 16));
                a[2] = __ldg(reinterpret_cast<const uint32_t*>(xp + kt * 16 + 8));
                a[3] = __ldg(reinterpret_cast<const uint32_t*>(xp + 8 * 512 + kt * 16 + 8));
#pragma unroll
                for (int n = 0; n < 4; n++) {
                    const unsigned short* w = wp[n >> 1] + kt * 256 + wo + (n & 1) * 8;
                    const uint32_t b0 = (uint32_t)__ldg(w) | ((uint32_t)__ldg(w + 16) << 16);
                    const uint32_t b1 = (uint32_t)__ldg(w + 128) | ((uint32_t)__ldg(w + 144) << 16);
                    mma16816(c[n], a, b0, b1);
                }
            }
#pragma unroll
            for (int n = 0; n < 4; n++) {
                bf16* dst = (n < 2 ? g_ka : g_va) + (size_t)(rb * 16 + (lane >> 2)) * 16 + (n & 1) * 8 + (lane & 3) * 2;
                *reinterpret_cast<uint32_t*>(dst) = pack_bf16(c[n][0], c[n][1]);
                *reinterpret_cast<uint32_t*>(dst + 8 * 16) = pack_bf16(c[n][2], c[n][3]);
            }
        }
    } else {
        const int wg = warp >> 2, wt = tid & 127, ww = warp & 3;
        const uint64_t dbase = (uint64_t)1 << 62 | (uint64_t)64 << 32;
        unsigned char* stg = sgen + P_STG + wg * 32768;
        const uint32_t stg_a = sb + P_STG + wg * 32768;
        unsigned* pend = nullptr;
        int it = 0;
        for (;;) {
            mbar_wait(full + (it % P_STAGES) * 8, (it / P_STAGES) & 1);
            const int t = tile_id[it % P_STAGES];
            if (t >= P_NT) break;
            float acc[2][64];
            for (int kt = 0; kt < 8; kt++, it++) {
                const int st = it % P_STAGES;
                if (kt) mbar_wait(full + st * 8, (it / P_STAGES) & 1);
                const uint32_t a = sb + st * P_STAGE;
                asm volatile("wgmma.fence.sync.aligned;" ::: "memory");
#pragma unroll
                for (int k = 0; k < 4; k++) {
                    const uint64_t db = dbase | ((uint64_t)512 << 16) | (uint64_t)(((a + 16384 + wg * 16384 + k * 2048) & 0x3FFFF) >> 4);
                    const uint64_t da0 = dbase | ((uint64_t)1 << 16) | (uint64_t)(((a + k * 32) & 0x3FFFF) >> 4);
                    const uint64_t da1 = dbase | ((uint64_t)1 << 16) | (uint64_t)(((a + 8192 + k * 32) & 0x3FFFF) >> 4);
                    wgmma128(acc[0], da0, db, kt | k);
                    wgmma128(acc[1], da1, db, kt | k);
                }
                asm volatile("wgmma.commit_group.sync.aligned;" ::: "memory");
                if (kt) {
                    asm volatile("wgmma.wait_group.sync.aligned 1;" ::: "memory");
                    if (lane == 0) mbar_arrive(empty + ((it - 1) % P_STAGES) * 8);
                }
                if (kt == 2 && pend) {
                    if (wt == 0) {
                        asm volatile("cp.async.bulk.wait_group 0;" ::: "memory");
                        __threadfence();
                        st_release_u32(pend, E + 1);
                    }
                    pend = nullptr;
                    __syncwarp();
                }
            }
            asm volatile("wgmma.wait_group.sync.aligned 0;" ::: "memory");
            if (lane == 0) mbar_arrive(empty + ((it - 1) % P_STAGES) * 8);
            if (wt == 0) asm volatile("cp.async.bulk.wait_group.read 0;" ::: "memory");
            asm volatile("bar.sync %0, 128;" ::"r"(1 + wg) : "memory");
#pragma unroll
            for (int hf = 0; hf < 2; hf++)
#pragma unroll
                for (int n = 0; n < 16; n++)
#pragma unroll
                    for (int u = 0; u < 2; u++) {
                        const int row = hf * 64 + ww * 16 + (lane >> 2) + u * 8;
                        *reinterpret_cast<uint32_t*>(stg + row * 256 + ((n ^ (row & 7)) << 4) + (lane & 3) * 4) =
                            pack_bf16(acc[hf][n * 4 + u * 2], acc[hf][n * 4 + u * 2 + 1]);
                    }
            if (t < P_NT1) {
                asm volatile("fence.proxy.async;" ::: "memory");
                asm volatile("bar.sync %0, 128;" ::"r"(1 + wg) : "memory");
                if (wt == 0) {
                    const int bn2 = t % 48, which = bn2 >> 4, h = (bn2 & 15) * 2 + wg, seg = (t / 48) * 4;
#pragma unroll
                    for (int q = 0; q < 4; q++)
                        asm volatile("cp.async.bulk.global.shared::cta.bulk_group [%0], [%1], 8192;"
                                     ::"l"(g_qkvx + (((size_t)which * 64 + seg + q) * 32 + h) * 4096), "r"(stg_a + q * 8192) : "memory");
                    asm volatile("cp.async.bulk.commit_group;" ::: "memory");
                }
            } else {
                asm volatile("bar.sync %0, 128;" ::"r"(1 + wg) : "memory");
                bf16* C = g_qa + (size_t)(((t - P_NT1) >> 1) * 128) * 512 + ((t - P_NT1) & 1) * 256 + wg * 128;
#pragma unroll 4
                for (int i = 0; i < 16; i++) {
                    const int c = wt + i * 128, row = c >> 4, ch = c & 15;
                    *reinterpret_cast<uint4*>(C + (size_t)row * 512 + ch * 8) = *reinterpret_cast<const uint4*>(stg + row * 256 + ((ch ^ (row & 7)) << 4));
                }
            }
            if (t < P_NT1) {
                const int bn2 = t % 48;
                pend = &g_pflag[((bn2 >> 4) * 16 + t / 48) * 32 + (bn2 & 15) * 2 + wg];
                if (it == 8 && wt == 0) {
                    asm volatile("cp.async.bulk.wait_group 0;" ::: "memory");
                    __threadfence();
                    st_release_u32(pend, E + 1);
                }
                if (it == 8) pend = nullptr;
                __syncwarp();
            }
        }
        if (pend && wt == 0) {
            asm volatile("cp.async.bulk.wait_group 0;" ::: "memory");
            __threadfence();
            st_release_u32(pend, E + 1);
        }
    }
    TL_END(1)
}

constexpr int AK_CHUNK = 256;
__global__ void __launch_bounds__(128, 4) attn_a_kernel() {
    __shared__ __align__(128) bf16 sk[2][AK_CHUNK * 16];
    __shared__ __align__(128) bf16 sv[2][AK_CHUNK * 16];
    const int tid = threadIdx.x, lane = tid & 31, warp = tid >> 5;
    const int qb = blockIdx.x >> 3, hg = blockIdx.x & 7;
    const int h = hg * 4 + warp;
    const int q0 = qb * 32;
    TL_BEG(4)
    asm volatile("griddepcontrol.launch_dependents;" ::: "memory");

    auto load_chunk = [&](int st, int c) {
#pragma unroll
        for (int i = 0; i < 4; i++) {
            int idx = tid + i * 128;
            int r = idx >> 1, ch = idx & 1;
            int pc = ch ^ ((r >> 2) & 1);
            cp_async16(smem_u32(&sk[st][r * 16 + pc * 8]), g_ka + (size_t)(c * AK_CHUNK + r) * 16 + ch * 8);
            cp_async16(smem_u32(&sv[st][r * 16 + pc * 8]), g_va + (size_t)(c * AK_CHUNK + r) * 16 + ch * 8);
        }
    };
    load_chunk(0, 0);
    cp_async_commit();

    uint32_t qf[2][4];
#pragma unroll
    for (int mt = 0; mt < 2; mt++) {
        const bf16* qp = g_qa + (size_t)(q0 + mt * 16 + (lane >> 2)) * 512 + h * 16 + (lane & 3) * 2;
        qf[mt][0] = *reinterpret_cast<const uint32_t*>(qp);
        qf[mt][1] = *reinterpret_cast<const uint32_t*>(qp + 8 * 512);
        qf[mt][2] = *reinterpret_cast<const uint32_t*>(qp + 8);
        qf[mt][3] = *reinterpret_cast<const uint32_t*>(qp + 8 * 512 + 8);
    }
    float o[2][3][4];
    float mx[2][2];
#pragma unroll
    for (int mt = 0; mt < 2; mt++) {
        mx[mt][0] = mx[mt][1] = -INFINITY;
#pragma unroll
        for (int n = 0; n < 3; n++)
#pragma unroll
            for (int c = 0; c < 4; c++) o[mt][n][c] = 0.f;
    }
    const uint32_t ones = (lane < 4) ? 0x3F803F80u : 0u;
    const float SC = 0.25f * 1.4426950408889634f;
    constexpr int NCH = 2048 / AK_CHUNK;
    for (int c = 0; c < NCH; c++) {
        cp_async_wait<0>();
        __syncthreads();
        if (c + 1 < NCH) load_chunk((c + 1) & 1, c + 1);
        cp_async_commit();
        const bf16* kk = sk[c & 1];
        const bf16* vv = sv[c & 1];
#pragma unroll 1
        for (int sb = 0; sb < AK_CHUNK / 64; sb++) {
            float s[2][8][4];
#pragma unroll
            for (int np = 0; np < 4; np++) {
                uint32_t b[4];
                int r = sb * 64 + np * 16 + (lane & 7) + (lane >> 4) * 8;
                int ch = (lane >> 3) & 1;
                int pc = ch ^ ((r >> 2) & 1);
                ldsm_x4(b[0], b[1], b[2], b[3], smem_u32(kk + r * 16 + pc * 8));
#pragma unroll
                for (int mt = 0; mt < 2; mt++) {
#pragma unroll
                    for (int e = 0; e < 4; e++) s[mt][np * 2][e] = s[mt][np * 2 + 1][e] = 0.f;
                    mma16816(s[mt][np * 2], qf[mt], b[0], b[1]);
                    mma16816(s[mt][np * 2 + 1], qf[mt], b[2], b[3]);
                }
            }
            uint32_t pf[2][4][4];
#pragma unroll
            for (int mt = 0; mt < 2; mt++) {
                float m0 = mx[mt][0], m1 = mx[mt][1];
#pragma unroll
                for (int n = 0; n < 8; n++) {
                    m0 = fmaxf(m0, fmaxf(s[mt][n][0], s[mt][n][1]));
                    m1 = fmaxf(m1, fmaxf(s[mt][n][2], s[mt][n][3]));
                }
                m0 = fmaxf(m0, __shfl_xor_sync(~0u, m0, 1)); m0 = fmaxf(m0, __shfl_xor_sync(~0u, m0, 2));
                m1 = fmaxf(m1, __shfl_xor_sync(~0u, m1, 1)); m1 = fmaxf(m1, __shfl_xor_sync(~0u, m1, 2));
                float a0 = ex2f((mx[mt][0] - m0) * SC), a1 = ex2f((mx[mt][1] - m1) * SC);
                mx[mt][0] = m0; mx[mt][1] = m1;
                float ms0 = m0 * SC, ms1 = m1 * SC;
#pragma unroll
                for (int n = 0; n < 8; n++) {
                    float p0 = ex2f(fmaf(s[mt][n][0], SC, -ms0)), p1 = ex2f(fmaf(s[mt][n][1], SC, -ms0));
                    float p2 = ex2f(fmaf(s[mt][n][2], SC, -ms1)), p3 = ex2f(fmaf(s[mt][n][3], SC, -ms1));
                    pf[mt][n >> 1][(n & 1) * 2] = pack_bf16(p0, p1);
                    pf[mt][n >> 1][(n & 1) * 2 + 1] = pack_bf16(p2, p3);
                }
#pragma unroll
                for (int n = 0; n < 3; n++) { o[mt][n][0] *= a0; o[mt][n][1] *= a0; o[mt][n][2] *= a1; o[mt][n][3] *= a1; }
            }
#pragma unroll
            for (int ks = 0; ks < 4; ks++) {
                uint32_t b[4];
                int r = sb * 64 + ks * 16 + (lane & 7) + ((lane >> 3) & 1) * 8;
                int ch = lane >> 4;
                int pc = ch ^ ((r >> 2) & 1);
                ldsm_x4_t(b[0], b[1], b[2], b[3], smem_u32(vv + r * 16 + pc * 8));
#pragma unroll
                for (int mt = 0; mt < 2; mt++) {
                    mma16816(o[mt][0], pf[mt][ks], b[0], b[1]);
                    mma16816(o[mt][1], pf[mt][ks], b[2], b[3]);
                    mma16816(o[mt][2], pf[mt][ks], ones, ones);
                }
            }
        }
    }
#pragma unroll
    for (int mt = 0; mt < 2; mt++) {
        const float l0 = __shfl_sync(~0u, o[mt][2][0], lane & ~3), l1 = __shfl_sync(~0u, o[mt][2][2], lane & ~3);
        float i0 = 1.f / l0, i1 = 1.f / l1;
#pragma unroll
        for (int n = 0; n < 2; n++) {
            bf16* dst = g_oa + (size_t)(q0 + mt * 16 + (lane >> 2)) * 512 + h * 16 + n * 8 + (lane & 3) * 2;
            *reinterpret_cast<uint32_t*>(dst) = pack_bf16(o[mt][n][0] * i0, o[mt][n][1] * i0);
            *reinterpret_cast<uint32_t*>(dst + 8 * 512) = pack_bf16(o[mt][n][2] * i1, o[mt][n][3] * i1);
        }
    }
    TL_END(4)
}

constexpr int R_KV = 0;
constexpr int R_KV_BUF = 48 * 256;
constexpr int R_QM = R_KV + 4 * R_KV_BUF;
constexpr int R_QX = R_QM + 2048;
constexpr int R_PART = R_QX + 8192;
constexpr int R_S = R_PART + 24576;
constexpr int R_O = R_S + 24 * 40 * 4;
constexpr int R_RED = R_O + 8 * 136 * 2;
constexpr int R_BAR = R_RED + 2048;
constexpr int R_MB = R_BAR + 256;
constexpr int R_WQS = 131072;
#define NPF 3
#define NPE 0
constexpr int R_BAR2 = R_WQS + 65536;
constexpr int R_SMEM = R_BAR2 + 64;

__global__ void __cluster_dims__(2, 1, 1) __launch_bounds__(256, 1)
rec_kernel(const __grid_constant__ CUtensorMap tmWq, const __grid_constant__ CUtensorMap tmWk, const __grid_constant__ CUtensorMap tmWv,
           const __grid_constant__ CUtensorMap tmWo, const bf16* __restrict__ mem0, const bf16* __restrict__ xb, bf16* __restrict__ out) {
    extern __shared__ __align__(1024) unsigned char sm[];
    const int tid = threadIdx.x, lane = tid & 31, warp = tid >> 5;
    const int cta = blockIdx.x, h = cta >> 1, j = cta & 1;
    const int kq = warp & 3, mh = warp >> 2;
    const uint32_t sbase = smem_u32(sm);
    const unsigned E = *(volatile unsigned*)&g_epoch;
    TL_BEG(0)

    uint32_t wq[4][8][4];
    uint32_t wo[2][8][4];
    {
        const uint32_t wb = sbase + R_BAR2;
        if (tid == 0) {
#pragma unroll
            for (int i = 0; i < 4; i++) mbar_init(wb + i * 8, 1);
            asm volatile("fence.mbarrier_init.release.cluster;" ::: "memory");
            asm volatile("fence.proxy.async;" ::: "memory");
#pragma unroll
            for (int m = 0; m < 3; m++) {
                mbar_expect(wb + m * 8, 65536);
                for (int b = 0; b < 8; b++)
                    tma2d(sbase + m * 65536 + b * 8192, m == 0 ? &tmWq : (m == 1 ? &tmWk : &tmWv), h * 128 + j * 64, b * 64, wb + m * 8);
            }
        }
        __syncthreads();
        const int fr = (lane & 7) + (lane >> 4) * 8, fc = (lane >> 3) & 1;
        auto frag_w = [&](int g, uint32_t (*f)[4]) {
            const uint32_t a = sbase + (g >> 2) * 65536 + (kq * 128 + fr) * 128 + ((((g & 3) * 2 + fc) ^ (lane & 7)) << 4);
#pragma unroll
            for (int kt = 0; kt < 8; kt++) ldsm_x4_t(f[kt][0], f[kt][1], f[kt][2], f[kt][3], a + kt * 2048);
        };
        mbar_wait(wb + mh * 8, 0);
#pragma unroll
        for (int i = 0; i < 4; i++)
            if (mh == 0 || i < 2) frag_w(mh * 6 + i, wq[i]);
        __syncthreads();
        if (tid == 0) {
            asm volatile("fence.proxy.async;" ::: "memory");
            mbar_expect(wb + 24, 65536);
            for (int b = 0; b < 8; b++) tma2d(sbase + b * 8192, &tmWo, j * 256 + (b & 3) * 64, h * 128 + (b >> 2) * 64, wb + 24);
        }
        mbar_wait(wb + 8 + mh * 8, 0);
#pragma unroll
        for (int i = 2; i < 4; i++)
            if (mh == 1) frag_w(6 + i, wq[i]);
        frag_w(mh * 6 + 4, wo[0]);
        frag_w(mh * 6 + 5, wo[1]);
        __syncthreads();
#pragma unroll
        for (int i = 0; i < 2; i++)
#pragma unroll
            for (int kt = 0; kt < 8; kt++)
                reinterpret_cast<uint4*>(sm + R_WQS)[((warp * 2 + i) * 8 + kt) * 32 + lane] = make_uint4(wo[i][kt][0], wo[i][kt][1], wo[i][kt][2], wo[i][kt][3]);
        mbar_wait(wb + 24, 0);
#pragma unroll
        for (int i = 0; i < 2; i++) {
            const int t = 2 * warp + i;
            const uint32_t a = sbase + (t >> 2) * 8192 + fr * 128 + ((((t & 3) * 2 + fc) ^ (lane & 7)) << 4);
#pragma unroll
            for (int kt = 0; kt < 8; kt++) ldsm_x4_t(wo[i][kt][0], wo[i][kt][1], wo[i][kt][2], wo[i][kt][3], a + (kt >> 2) * 32768 + (kt & 3) * 2048);
        }
    }
    __syncthreads();
    for (int i = tid; i < 4 * 128; i += 256) {
        int b = i >> 7, c = i & 127;
        *reinterpret_cast<uint4*>(sm + R_KV + b * R_KV_BUF + 40 * 256 + c * 16) = make_uint4(0, 0, 0, 0);
    }
    if (tid < 88) st_relaxed_v4(g_fin + cta * 88 + tid, 0u, 0u, 0u, 0u);
    const uint32_t bar = sbase + R_BAR;
    if (tid == 0) {
        mbar_init(bar, 1);
        mbar_init(bar + 8, 1);
        mbar_init(bar + 16, 1);
        mbar_init(bar + 24, 1);
        mbar_arrive(bar + 16);
        mbar_arrive(bar);
        mbar_expect(bar, 24576);
        asm volatile("fence.mbarrier_init.release.cluster;" ::: "memory");
    }
    asm volatile("barrier.cluster.arrive.release.aligned;\nbarrier.cluster.wait.acquire.aligned;" ::: "memory");
    const uint32_t rbase = mapa(sbase, j ^ 1);
    const uint32_t lbase = mapa(sbase, j);

    auto wait_tile = [&](int t) {
        const int i = tid - 224;
        const unsigned* f = &g_pflag[((i % 3) * 16 + t + i / 3) * 32 + h];
        int it = 0;
        while (ld_acquire_u32(f) != E + 1 && it < SPIN_LIMIT) it++;
    };
    auto prefetch = [&](int s) {
        const int par = s & 1;
        const uint32_t pb = bar + 16 + par * 8;
        const uint32_t kd = sbase + R_KV + (par * 2) * R_KV_BUF + 8 * 256;
        mbar_expect(pb, 20480);
        bulk_g2s(kd, g_qkvx + (((size_t)1 * 64 + s) * 32 + h) * 4096, 8192, pb);
        bulk_g2s(sbase + R_QX + par * 4096, g_qkvx + (((size_t)0 * 64 + s) * 32 + h) * 4096 + j * 16 * 128, 4096, pb);
        bulk_g2s(kd + R_KV_BUF, g_qkvx + (((size_t)2 * 64 + s) * 32 + h) * 4096, 8192, pb);
    };

    {
        uint32_t xf[8][2];
        auto load_x = [&](int p, uint32_t (*f)[2]) {
#pragma unroll
            for (int kt = 0; kt < 8; kt++) {
                const bf16* g = xb + (8 * p + (lane >> 2)) * 512 + (kq * 8 + kt) * 16 + (lane & 3) * 2;
                f[kt][0] = *reinterpret_cast<const uint32_t*>(g);
                f[kt][1] = *reinterpret_cast<const uint32_t*>(g + 8);
            }
        };
        load_x(0, xf);
#pragma unroll 1
        for (int p = 0; p < 4; p++) {
            float c[6][4];
#pragma unroll
            for (int i = 0; i < 6; i++) c[i][0] = c[i][1] = c[i][2] = c[i][3] = 0.f;
            const uint4* ws = reinterpret_cast<const uint4*>(sm + R_WQS) + warp * 512 + lane;
#pragma unroll
            for (int kt = 0; kt < 8; kt++) {
                const uint4 f0 = ws[kt * 32], f1 = ws[256 + kt * 32];
                const uint32_t b0 = xf[kt][0], b1 = xf[kt][1];
#pragma unroll
                for (int i = 0; i < 4; i++) mma16816(c[i], wq[i][kt], b0, b1);
                const uint32_t a0[4] = {f0.x, f0.y, f0.z, f0.w}, a1[4] = {f1.x, f1.y, f1.z, f1.w};
                mma16816(c[4], a0, b0, b1);
                mma16816(c[5], a1, b0, b1);
            }
            if (p < 3) load_x(p + 1, xf);
            float4* part = reinterpret_cast<float4*>(sm + R_PART) + (kq * 12 + mh * 6) * 32 + lane;
#pragma unroll
            for (int i = 0; i < 6; i++) part[i * 32] = make_float4(c[i][0], c[i][1], c[i][2], c[i][3]);
            __syncthreads();
            if (tid < 192) {
                const bool odd = (lane >> 2) & 1;
                const int row = (lane & 3) * 2 + (odd ? 1 : 0), mat = warp >> 1;
                const int ch = j * 8 + (warp & 1) * 4 + (lane >> 3);
                const uint32_t in = row * 256 + ((ch ^ row) << 4);
                const uint32_t kv = R_KV + (mat - 1) * R_KV_BUF + (8 + 8 * p) * 256, qx = R_QX + (p & 1) * 2048;
                const uint32_t xl = lbase + in + (mat ? kv : ((p >> 1) == j ? qx : R_QM));
                const uint32_t xr = rbase + in + (mat ? kv : ((p >> 1) != j ? qx : R_QM));
                const uint32_t pa = sbase + R_PART + (warp * 64 + lane) * 16;
                uint32_t pv[4];
#pragma unroll
                for (int u = 0; u < 2; u++) {
                    float4 q[4];
#pragma unroll
                    for (int w = 0; w < 4; w++) q[w] = lds128(pa + w * 6144 + u * 512);
                    const float x = (q[0].x + q[1].x) + (q[2].x + q[3].x), y = (q[0].y + q[1].y) + (q[2].y + q[3].y);
                    const float z = (q[0].z + q[1].z) + (q[2].z + q[3].z), w = (q[0].w + q[1].w) + (q[2].w + q[3].w);
                    const float r0 = __shfl_xor_sync(~0u, odd ? x : y, 4), r1 = __shfl_xor_sync(~0u, odd ? z : w, 4);
                    pv[2 * u] = pack_bf16(odd ? r0 : x, odd ? y : r0);
                    pv[2 * u + 1] = pack_bf16(odd ? r1 : z, odd ? w : r1);
                }
                const bool t0 = lane & 8, t1 = lane & 16;
                const uint32_t r1 = __shfl_xor_sync(~0u, t0 ? pv[0] : pv[1], 8), r2 = __shfl_xor_sync(~0u, t0 ? pv[2] : pv[3], 8);
                const uint32_t a0 = t0 ? r1 : pv[0], a1 = t0 ? pv[1] : r1, b0 = t0 ? r2 : pv[2], b1 = t0 ? pv[3] : r2;
                const uint32_t r3 = __shfl_xor_sync(~0u, t1 ? a0 : b0, 16), r4 = __shfl_xor_sync(~0u, t1 ? a1 : b1, 16);
                const uint32_t w0 = t1 ? r3 : a0, w1 = t1 ? r4 : a1, w2 = t1 ? b0 : r3, w3 = t1 ? b1 : r4;
                st_async_v4(xr, w0, w1, w2, w3, rbase + R_BAR);
                st_async_v4(xl, w0, w1, w2, w3, lbase + R_BAR);
            }
            if (p == 3) mbar_wait(bar, 1); else __syncthreads();
        }
    }
    TL_BEG(7)
    PROF_DECL

    for (int s = 0; s < 64; s++) {
        const int par = s & 1;
        const uint32_t k_addr = sbase + R_KV + (par * 2) * R_KV_BUF;
        const uint32_t v_addr = k_addr + R_KV_BUF;
        if (tid == 0) mbar_expect(bar, 6144);

        uint32_t mb[8][2];
        uint32_t pf[NPF][2][4];
        auto pref = [&](int k0, int k1) {
            const uint32_t wa = sbase + R_WQS + (warp * 512 + lane) * 16;
#pragma unroll
            for (int kt = 0; kt < NPF; kt++)
                if (kt >= k0 && kt < k1)
#pragma unroll
                for (int i = 0; i < 2; i++)
                    asm volatile("ld.shared.v4.u32 {%0,%1,%2,%3}, [%4];" : "=r"(pf[kt][i][0]), "=r"(pf[kt][i][1]), "=r"(pf[kt][i][2]), "=r"(pf[kt][i][3])
                                 : "r"(wa + kt * 512 + i * 4096));
        };
        if (s == 0) {
            pref(0, NPF);
#pragma unroll
            for (int kt = 0; kt < 8; kt++) {
                const bf16* p = mem0 + (lane >> 2) * 512 + (kq * 8 + kt) * 16 + (lane & 3) * 2;
                mb[kt][0] = *reinterpret_cast<const uint32_t*>(p);
                mb[kt][1] = *reinterpret_cast<const uint32_t*>(p + 8);
            }
        } else {
            if (tid == 0) mbar_expect(bar + 8, 8192);
            const uint4* p = g_acc + (s & 3) * 2048 + (j * 8 + warp) * 96 + lane;
            constexpr unsigned FULL = 0x42000000u;
            uint4 a[3];
#pragma unroll
            for (int i = 0; i < 3; i++) a[i] = ld_relaxed_v4(p + i * 32);
            pref(0, NPE);
            int it = 0;
            bool bad;
            do {
                bad = false;
#pragma unroll
                for (int i = 0; i < 3; i++)
                    if (a[i].w != FULL) { a[i] = ld_relaxed_v4(p + i * 32); bad = true; }
                it++;
            } while (bad && it < SPIN_LIMIT);
            const uint32_t m0 = pack_bf16(__uint_as_float(a[0].x), __uint_as_float(a[0].y)), m1 = pack_bf16(__uint_as_float(a[0].z), __uint_as_float(a[1].x));
            const uint32_t m2 = pack_bf16(__uint_as_float(a[1].y), __uint_as_float(a[1].z)), m3 = pack_bf16(__uint_as_float(a[2].x), __uint_as_float(a[2].y));
            const uint32_t off = R_MB + ((j * 8 + warp) * 32 + lane) * 16;
            st_async_v4(rbase + off, m0, m1, m2, m3, rbase + R_BAR + 8);
            st_async_v4(lbase + off, m0, m1, m2, m3, lbase + R_BAR + 8);
            pref(NPE, NPF);
            mbar_wait(bar + 8, (s - 1) & 1);
            const uint4* q = reinterpret_cast<const uint4*>(sm + R_MB) + kq * 128 + lane;
#pragma unroll
            for (int i = 0; i < 4; i++) {
                const uint4 t = q[i * 32];
                mb[2 * i][0] = t.x; mb[2 * i][1] = t.y; mb[2 * i + 1][0] = t.z; mb[2 * i + 1][1] = t.w;
            }
        }

        PROF(0)
        {
            float c[6][4];
#pragma unroll
            for (int i = 0; i < 6; i++) c[i][0] = c[i][1] = c[i][2] = c[i][3] = 0.f;
            const uint4* ws = reinterpret_cast<const uint4*>(sm + R_WQS) + warp * 512 + lane;
#pragma unroll
            for (int kt = 0; kt < 8; kt++) {
                if (kt < NPF) {
#pragma unroll
                    for (int i = 0; i < 4; i++) mma16816(c[i], wq[i][kt], mb[kt][0], mb[kt][1]);
                    mma16816(c[4], pf[kt][0], mb[kt][0], mb[kt][1]);
                    mma16816(c[5], pf[kt][1], mb[kt][0], mb[kt][1]);
                } else {
                    const uint4 f0 = ws[kt * 32], f1 = ws[256 + kt * 32];
#pragma unroll
                    for (int i = 0; i < 4; i++) mma16816(c[i], wq[i][kt], mb[kt][0], mb[kt][1]);
                    const uint32_t a0[4] = {f0.x, f0.y, f0.z, f0.w}, a1[4] = {f1.x, f1.y, f1.z, f1.w};
                    mma16816(c[4], a0, mb[kt][0], mb[kt][1]);
                    mma16816(c[5], a1, mb[kt][0], mb[kt][1]);
                }
            }
            float4* part = reinterpret_cast<float4*>(sm + R_PART) + (kq * 12 + mh * 6) * 32 + lane;
#pragma unroll
            for (int i = 0; i < 6; i++) part[i * 32] = make_float4(c[i][0], c[i][1], c[i][2], c[i][3]);
        }
        const bool odd = (lane >> 2) & 1;
        uint32_t xo0, xo1, pa;
        {
            const int row = (lane & 3) * 2 + (odd ? 1 : 0);
            const int mat = warp >> 1;
            const int ch = j * 8 + (warp & 1) * 4 + (lane >> 3);
            const uint32_t off = ((mat == 0) ? R_QM : (R_KV + (par * 2 + mat - 1) * R_KV_BUF)) + row * 256;
            xo0 = off + ((ch ^ row) << 4);
            xo1 = rbase + xo0;
            xo0 += lbase;
            pa = sbase + R_PART + (warp * 64 + lane) * 16;
            asm volatile("" : "+r"(xo0), "+r"(xo1), "+r"(pa));
        }
        const int r = lane >> 2, c2 = (lane & 3) * 2;
        const float scale = 0.08838834764831845f;
        auto tok_s = [&](int nt, int NT) {
            const uint32_t qa = sbase + R_QX + par * 4096 + (lane & 15) * 256 + (((lane >> 4) ^ (lane & 7)) << 4);
            const uint32_t ka = k_addr + (nt * 8 + (lane & 7)) * 256 + (((lane >> 3) ^ (lane & 7)) << 4);
            const uint32_t sa = sbase + R_S + (8 + r) * 112 + (nt * 8 + c2) * 2;
            uint32_t af[8][4];
#pragma unroll
            for (int t = 0; t < 8; t++) ldsm_x4(af[t][0], af[t][1], af[t][2], af[t][3], qa ^ (t * 32));
#pragma unroll 1
            for (int q = 0; q < NT; q++) {
                float c0[4] = {0, 0, 0, 0}, c1[4] = {0, 0, 0, 0};
                uint32_t kb[4][4];
#pragma unroll
                for (int i = 0; i < 4; i++) ldsm_x4(kb[i][0], kb[i][1], kb[i][2], kb[i][3], (ka ^ (i * 64)) + q * 2048);
#pragma unroll
                for (int i = 0; i < 4; i++) {
                    mma16816(c0, af[2 * i], kb[i][0], kb[i][1]);
                    mma16816(c1, af[2 * i + 1], kb[i][2], kb[i][3]);
                }
                const uint32_t x = pack_bf16(c0[0] + c1[0], c0[1] + c1[1]), y = pack_bf16(c0[2] + c1[2], c0[3] + c1[3]);
                sts32(sa + q * 16, pack_bf16(bf_lo(x) * scale, bf_hi(x) * scale));
                sts32(sa + q * 16 + 8 * 112, pack_bf16(bf_lo(y) * scale, bf_hi(y) * scale));
            }
        };
        __syncthreads();
        PROF(1)
        if (tid < 192) {
            float4 v[8];
#pragma unroll
            for (int w = 0; w < 4; w++) { v[w] = lds128(pa + w * 6144); v[4 + w] = lds128(pa + w * 6144 + 512); }
            uint32_t pv[4];
#pragma unroll
            for (int u = 0; u < 2; u++) {
                const float4* q = v + u * 4;
                const float x = (q[0].x + q[1].x) + (q[2].x + q[3].x), y = (q[0].y + q[1].y) + (q[2].y + q[3].y);
                const float z = (q[0].z + q[1].z) + (q[2].z + q[3].z), w = (q[0].w + q[1].w) + (q[2].w + q[3].w);
                const float r0 = __shfl_xor_sync(~0u, odd ? x : y, 4), r1 = __shfl_xor_sync(~0u, odd ? z : w, 4);
                pv[2 * u] = pack_bf16(odd ? r0 : x, odd ? y : r0);
                pv[2 * u + 1] = pack_bf16(odd ? r1 : z, odd ? w : r1);
            }
            const bool t0 = lane & 8, t1 = lane & 16;
            const uint32_t r1 = __shfl_xor_sync(~0u, t0 ? pv[0] : pv[1], 8), r2 = __shfl_xor_sync(~0u, t0 ? pv[2] : pv[3], 8);
            const uint32_t a0 = t0 ? r1 : pv[0], a1 = t0 ? pv[1] : r1, b0 = t0 ? r2 : pv[2], b1 = t0 ? pv[3] : r2;
            const uint32_t r3 = __shfl_xor_sync(~0u, t1 ? a0 : b0, 16), r4 = __shfl_xor_sync(~0u, t1 ? a1 : b1, 16);
            const uint32_t w0 = t1 ? r3 : a0, w1 = t1 ? r4 : a1, w2 = t1 ? b0 : r3, w3 = t1 ? b1 : r4;
            st_async_v4(xo1, w0, w1, w2, w3, rbase + R_BAR);
            st_async_v4(xo0, w0, w1, w2, w3, lbase + R_BAR);
        } else {
            constexpr unsigned long long SIG = (1ull << 44) | (1ull << 56) | (1ull << 60);
            constexpr unsigned long long CHK = (1ull << 0) | (1ull << 3) | (1ull << 7) | (1ull << 15) | (1ull << 31);
            if (((SIG >> s) & 1) && tid == 200) { __threadfence(); atomicAdd(&g_oxcnt[(s - 1) >> 2], 1u); }
            if (((CHK >> s) & 1) && tid >= 224 && tid < 224 + 3 * (s < 7 ? 1 : (s + 1) >> 2)) wait_tile((s + 1) >> 2);
            if (warp == 6 && lane < 24) st_relaxed_v4(g_acc + ((s + 3) & 3) * 2048 + cta * 24 + lane, 0u, 0u, 0u, 0u);
            __syncwarp();
            mbar_wait(bar + 16 + par * 8, (s >> 1) & 1);
            tok_s(1 + (warp - 6) * 2, 2);
        }
        PROF(2)
        uint32_t qa, ka, sa, va, sr;
        {
            qa = sbase + R_QM + (lane & 7) * 256 + (((lane >> 3) ^ (lane & 7)) << 4);
            ka = k_addr + (warp * 16 + (lane & 15)) * 256 + (((lane >> 4) ^ (lane & 7)) << 4);
            sa = sbase + R_S + c2 * 112 + (warp * 16 + r) * 2;
            const int vrow = (lane & 7) + ((lane >> 3) & 1) * 8;
            va = v_addr + vrow * 256 + (((2 * warp + (lane >> 4)) ^ (vrow & 7)) << 4);
            sr = sbase + R_S + r * 112 + c2 * 2;
            asm volatile("" : "+r"(qa), "+r"(ka), "+r"(sa), "+r"(va), "+r"(sr));
        }
        mbar_wait(bar + 16 + par * 8, (s >> 1) & 1);
        mbar_wait(bar, par);
        PROF(3)

        PROF(4)
        {
            if (warp < 3) {
                uint32_t af[8][4], qb[4][4];
#pragma unroll
                for (int i = 0; i < 4; i++) {
                    ldsm_x4(qb[i][0], qb[i][1], qb[i][2], qb[i][3], qa ^ (i * 64));
                    ldsm_x4(af[2 * i][0], af[2 * i][1], af[2 * i][2], af[2 * i][3], ka ^ (i * 64));
                    ldsm_x4(af[2 * i + 1][0], af[2 * i + 1][1], af[2 * i + 1][2], af[2 * i + 1][3], ka ^ (i * 64 + 32));
                }
                float c0[4] = {0, 0, 0, 0}, c1[4] = {0, 0, 0, 0};
#pragma unroll
                for (int i = 0; i < 4; i++) {
                    mma16816(c0, af[2 * i], qb[i][0], qb[i][1]);
                    mma16816(c1, af[2 * i + 1], qb[i][2], qb[i][3]);
                }
                const uint32_t x = pack_bf16(c0[0] + c1[0], c0[1] + c1[1]), y = pack_bf16(c0[2] + c1[2], c0[3] + c1[3]);
                const uint32_t x2 = pack_bf16(bf_lo(x) * scale, bf_hi(x) * scale), y2 = pack_bf16(bf_lo(y) * scale, bf_hi(y) * scale);
                asm volatile("st.shared.u16 [%0], %1;" ::"r"(sa), "h"((unsigned short)(x2 & 0xffff)) : "memory");
                asm volatile("st.shared.u16 [%0], %1;" ::"r"(sa + 112), "h"((unsigned short)(x2 >> 16)) : "memory");
                if (warp < 2) {
                    asm volatile("st.shared.u16 [%0], %1;" ::"r"(sa + 16), "h"((unsigned short)(y2 & 0xffff)) : "memory");
                    asm volatile("st.shared.u16 [%0], %1;" ::"r"(sa + 128), "h"((unsigned short)(y2 >> 16)) : "memory");
                }
            } else if (warp == 3) {
                tok_s(0, 1);
            }
            uint32_t vb[3][4];
#pragma unroll
            for (int ks = 0; ks < 3; ks++) ldsm_x4_t(vb[ks][0], vb[ks][1], vb[ks][2], vb[ks][3], va + ks * 4096);
            uint32_t oa = sbase + R_O + r * 272 + (warp * 16 + c2) * 2;
            uint32_t ob = sbase + R_O + (lane & 7) * 272 + (lane >> 3) * 16;
            uint4* dst = g_acc + ((s + 1) & 3) * 2048 + (8 * j + warp) * 96 + (c2 + (r & 1)) * 4 + (r >> 1);
            asm volatile("" : "+r"(oa), "+r"(ob), "+l"(dst));
            PROF(8)
            __syncthreads();
            PROF(9)
            const float L2E = 1.4426950408889634f;
            auto soft = [&](auto NRc, const int* ro, const int* kmax, uint32_t (*p)[5]) {
                constexpr int NR = decltype(NRc)::value;
                float sv[NR][10], m[NR], l[NR];
#pragma unroll
                for (int q = 0; q < NR; q++)
#pragma unroll
                    for (int t = 0; t < 5; t++) {
                        const uint32_t u = lds32(sr + ro[q] * 112 + t * 16);
                        sv[q][2 * t] = bf_lo(u); sv[q][2 * t + 1] = bf_hi(u);
                    }
#pragma unroll
                for (int q = 0; q < NR; q++) {
                    if (NR == 2) {
#pragma unroll
                        for (int t = 0; t < 5; t++) {
                            if (t * 8 + c2 > kmax[q]) sv[q][2 * t] = -INFINITY;
                            if (t * 8 + c2 + 1 > kmax[q]) sv[q][2 * t + 1] = -INFINITY;
                        }
                    }
                    m[q] = fmaxf(fmaxf(fmaxf(sv[q][0], sv[q][1]), fmaxf(sv[q][2], sv[q][3])), fmaxf(fmaxf(sv[q][4], sv[q][5]), fmaxf(sv[q][6], sv[q][7])));
                    m[q] = fmaxf(m[q], fmaxf(sv[q][8], sv[q][9]));
                }
#pragma unroll
                for (int q = 0; q < NR; q++) m[q] = fmaxf(m[q], __shfl_xor_sync(~0u, m[q], 1));
#pragma unroll
                for (int q = 0; q < NR; q++) m[q] = fmaxf(m[q], __shfl_xor_sync(~0u, m[q], 2));
#pragma unroll
                for (int q = 0; q < NR; q++) {
                    const float ml = m[q] * L2E;
#pragma unroll
                    for (int t = 0; t < 10; t++) sv[q][t] = ex2f(fmaf(sv[q][t], L2E, -ml));
                    l[q] = ((sv[q][0] + sv[q][1]) + (sv[q][2] + sv[q][3])) + ((sv[q][4] + sv[q][5]) + (sv[q][6] + sv[q][7])) + (sv[q][8] + sv[q][9]);
                }
#pragma unroll
                for (int q = 0; q < NR; q++) l[q] += __shfl_xor_sync(~0u, l[q], 1);
#pragma unroll
                for (int q = 0; q < NR; q++) l[q] += __shfl_xor_sync(~0u, l[q], 2);
#pragma unroll
                for (int q = 0; q < NR; q++) {
                    const float inv = rcpf(l[q]);
#pragma unroll
                    for (int t = 0; t < 5; t++) p[q][t] = pack_bf16(sv[q][2 * t] * inv, sv[q][2 * t + 1] * inv);
                }
            };
            if (s < 63) {
                float o0[4] = {0, 0, 0, 0}, o1[4] = {0, 0, 0, 0};
                uint32_t pp[1][5];
                const int ro[1] = {0}, km[1] = {39};
                soft(std::integral_constant<int, 1>{}, ro, km, pp);
                const uint32_t* p = pp[0];
#pragma unroll
                for (int ks = 0; ks < 3; ks++) {
                    const uint32_t a[4] = {p[2 * ks], 0u, (ks < 2) ? p[2 * ks + 1] : 0u, 0u};
                    mma16816(o0, a, vb[ks][0], vb[ks][1]);
                    mma16816(o1, a, vb[ks][2], vb[ks][3]);
                }
                sts32(oa, pack_bf16(o0[0], o0[1]));
                sts32(oa + 16, pack_bf16(o1[0], o1[1]));
                __syncthreads();
                PROF(5)
                float c[2][2][4] = {};
#pragma unroll
                for (int i = 0; i < 4; i++) {
                    uint32_t b[4];
                    ldsm_x4(b[0], b[1], b[2], b[3], ob + i * 64);
#pragma unroll
                    for (int u = 0; u < 2; u++) {
                        mma16816(c[u][0], wo[u][2 * i], b[0], b[1]);
                        mma16816(c[u][1], wo[u][2 * i + 1], b[2], b[3]);
                    }
                }
                float e[2][4];
#pragma unroll
                for (int u = 0; u < 2; u++) {
                    const float x = c[u][0][0] + c[u][1][0], y = c[u][0][1] + c[u][1][1], z = c[u][0][2] + c[u][1][2], w = c[u][0][3] + c[u][1][3];
                    const float r0 = __shfl_xor_sync(~0u, odd ? x : y, 4), r1 = __shfl_xor_sync(~0u, odd ? z : w, 4);
                    e[u][0] = odd ? r0 : x; e[u][1] = odd ? y : r0; e[u][2] = odd ? r1 : z; e[u][3] = odd ? w : r1;
                }
                red_add_v4(dst, e[0][0], e[0][1], e[0][2], 1.f);
                red_add_v4(dst + 32, e[0][3], e[1][0], e[1][1], 1.f);
                red_add_v4(dst + 64, e[1][2], e[1][3], 0.f, 1.f);
                PROF(6)
            }
            {
                float o0[4] = {0, 0, 0, 0}, o1[4] = {0, 0, 0, 0};
                uint32_t pp[2][5];
                const int ro[2] = {8, 16}, km[2] = {8 + 16 * j + r, 16 + 16 * j + r};
                soft(std::integral_constant<int, 2>{}, ro, km, pp);
                const uint32_t *p = pp[0], *q = pp[1];
#pragma unroll
                for (int ks = 0; ks < 3; ks++) {
                    const uint32_t a[4] = {p[2 * ks], q[2 * ks], (ks < 2) ? p[2 * ks + 1] : 0u, (ks < 2) ? q[2 * ks + 1] : 0u};
                    mma16816(o0, a, vb[ks][0], vb[ks][1]);
                    mma16816(o1, a, vb[ks][2], vb[ks][3]);
                }
                if (s < 63) {
                    bf16* ox = g_ox + (size_t)(s * 32 + j * 16 + r) * 4096 + h * 128 + warp * 16 + c2;
                    *reinterpret_cast<uint32_t*>(ox) = pack_bf16(o0[0], o0[1]);
                    *reinterpret_cast<uint32_t*>(ox + 8) = pack_bf16(o1[0], o1[1]);
                    *reinterpret_cast<uint32_t*>(ox + 8 * 4096) = pack_bf16(o0[2], o0[3]);
                    *reinterpret_cast<uint32_t*>(ox + 8 * 4096 + 8) = pack_bf16(o1[2], o1[3]);
                    if (s >= 61) {
                        __syncwarp();
                        if (lane == 0) { __threadfence(); atomicAdd(&g_oxcnt[s - 46], 1u); }
                    }
                } else {
                    const uint32_t to = R_PART + (j * 16 + r) * 272 + (warp * 16 + c2) * 2;
#pragma unroll
                    for (int q = 0; q < 2; q++) {
                        const uint32_t b = (q ? rbase : lbase) + to;
                        st_cluster32(b, pack_bf16(o0[0], o0[1]));
                        st_cluster32(b + 16, pack_bf16(o1[0], o1[1]));
                        st_cluster32(b + 8 * 272, pack_bf16(o0[2], o0[3]));
                        st_cluster32(b + 8 * 272 + 16, pack_bf16(o1[2], o1[3]));
                    }
                }
            }
        }

        if (s < 63) {
            PROF(7)
            if (tid == 255) prefetch(s + 1);
            __syncwarp();
            PROF(10)
        }
    }
    asm volatile("barrier.cluster.arrive.release.aligned;\nbarrier.cluster.wait.acquire.aligned;" ::: "memory");
    TL_BEG(12) TL_END(12)
    {
        float e[33];
        e[32] = 0.f;
#pragma unroll
        for (int nt = 0; nt < 4; nt++) {
            float c[2][2][4] = {};
            const uint32_t ob = sbase + R_PART + (nt * 8 + (lane & 7)) * 272 + (lane >> 3) * 16;
#pragma unroll
            for (int i = 0; i < 4; i++) {
                uint32_t b[4];
                ldsm_x4(b[0], b[1], b[2], b[3], ob + i * 64);
#pragma unroll
                for (int u = 0; u < 2; u++) {
                    mma16816(c[u][0], wo[u][2 * i], b[0], b[1]);
                    mma16816(c[u][1], wo[u][2 * i + 1], b[2], b[3]);
                }
            }
#pragma unroll
            for (int u = 0; u < 2; u++)
#pragma unroll
                for (int q = 0; q < 4; q++) e[nt * 8 + u * 4 + q] = c[u][0][q] + c[u][1][q];
        }
        uint4* dst = g_fin + (j * 8 + warp) * 352 + lane;
#pragma unroll
        for (int v = 0; v < 11; v++) red_add_v4(dst + v * 32, e[3 * v], e[3 * v + 1], e[3 * v + 2], 1.f);
        if (tid < 88) {
            const int id = cta * 88 + tid, ln = id & 31, v = (id >> 5) % 11, ww = (id >> 5) / 11;
            uint4 a = ld_relaxed_v4(g_fin + id);
            int it = 0;
            while (a.w != 0x42000000u && it < SPIN_LIMIT) { a = ld_relaxed_v4(g_fin + id); it++; }
            const uint32_t val[3] = {a.x, a.y, a.z};
#pragma unroll
            for (int q = 0; q < 3; q++) {
                const int idx = v * 3 + q;
                if (idx < 32) {
                    const int col = ww * 32 + ((idx >> 2) & 1) * 16 + (ln >> 2) + ((idx >> 1) & 1) * 8;
                    const int tok = (idx >> 3) * 8 + (ln & 3) * 2 + (idx & 1);
                    out[(size_t)(2016 + tok) * 1024 + 512 + col] = __float2bfloat16_rn(__uint_as_float(val[q]));
                }
            }
        }
    }
    TL_END(0)
    PROF_END
}

typedef CUresult (*EncodeFn)(CUtensorMap*, CUtensorMapDataType, cuuint32_t, void*, const cuuint64_t*, const cuuint64_t*,
                             const cuuint32_t*, const cuuint32_t*, CUtensorMapInterleave, CUtensorMapSwizzle,
                             CUtensorMapL2promotion, CUtensorMapFloatOOBfill);
static void make_map(EncodeFn fn, CUtensorMap* m, const void* ptr, uint64_t inner, uint64_t outer, uint32_t box_inner, uint32_t box_outer) {
    cuuint64_t dims[2] = {inner, outer};
    cuuint64_t strides[1] = {inner * 2};
    cuuint32_t box[2] = {box_inner, box_outer};
    cuuint32_t es[2] = {1, 1};
    fn(m, CU_TENSOR_MAP_DATA_TYPE_BFLOAT16, 2, const_cast<void*>(ptr), dims, strides, box, es, CU_TENSOR_MAP_INTERLEAVE_NONE,
       CU_TENSOR_MAP_SWIZZLE_128B, CU_TENSOR_MAP_L2_PROMOTION_L2_128B, CU_TENSOR_MAP_FLOAT_OOB_FILL_NONE);
}

extern "C" void kernel_launch(void* const* d_in, const int* in_sizes, int n_in, void* d_out, int out_size) {
    const bf16* A_x = (const bf16*)d_in[0];
    const bf16* A_wq = (const bf16*)d_in[1];
    const bf16* A_wk = (const bf16*)d_in[2];
    const bf16* A_wv = (const bf16*)d_in[3];
    const bf16* A_wo = (const bf16*)d_in[4];
    const bf16* B_x = (const bf16*)d_in[5];
    const bf16* B_mem0 = (const bf16*)d_in[6];
    const bf16* B_Wq = (const bf16*)d_in[7];
    const bf16* B_Wk = (const bf16*)d_in[8];
    const bf16* B_Wv = (const bf16*)d_in[9];
    const bf16* B_Wo = (const bf16*)d_in[10];
    bf16* out = (bf16*)d_out;

    static bool init = false;
    static cudaStream_t s1, s2;
    static cudaEvent_t e0, e1, e2, e3, e4;
    static int nsm = 132;
    static bf16 *p_ox, *p_qa, *p_oa;
    static EncodeFn enc;
    if (!init) {
        cudaStreamCreateWithFlags(&s1, cudaStreamNonBlocking);
        cudaEventCreateWithFlags(&e0, cudaEventDisableTiming);
        cudaEventCreateWithFlags(&e1, cudaEventDisableTiming);
        cudaFuncSetAttribute(gemm_wg<0>, cudaFuncAttributeMaxDynamicSharedMemorySize, W_SMEM);
        cudaFuncSetAttribute(gemm_wg<2>, cudaFuncAttributeMaxDynamicSharedMemorySize, W_SMEM);
        cudaFuncSetAttribute(gemm_proj, cudaFuncAttributeMaxDynamicSharedMemorySize, P_SMEM);
        int dev = 0;
        cudaGetDevice(&dev);
        cudaDeviceGetAttribute(&nsm, cudaDevAttrMultiProcessorCount, dev);
        cudaStreamCreateWithFlags(&s2, cudaStreamNonBlocking);
        cudaEventCreateWithFlags(&e2, cudaEventDisableTiming);
        cudaEventCreateWithFlags(&e3, cudaEventDisableTiming);
        cudaEventCreateWithFlags(&e4, cudaEventDisableTiming);
        cudaFuncSetAttribute(rec_kernel, cudaFuncAttributeMaxDynamicSharedMemorySize, R_SMEM);
        cudaFuncSetAttribute(rec_kernel, cudaFuncAttributePreferredSharedMemoryCarveout, 100);
        cudaFuncSetAttribute(gemm_wg<0>, cudaFuncAttributePreferredSharedMemoryCarveout, 100);
        cudaFuncSetAttribute(gemm_wg<2>, cudaFuncAttributePreferredSharedMemoryCarveout, 100);
        cudaFuncSetAttribute(attn_a_kernel, cudaFuncAttributePreferredSharedMemoryCarveout, 100);
        cudaGetSymbolAddress((void**)&p_ox, g_ox);
        cudaGetSymbolAddress((void**)&p_qa, g_qa);
        cudaGetSymbolAddress((void**)&p_oa, g_oa);
        cudaDriverEntryPointQueryResult qr;
        cudaGetDriverEntryPoint("cuTensorMapEncodeTiled", (void**)&enc, cudaEnableDefault, &qr);
        init = true;
    }
    CUtensorMap m_bx, m_wq, m_wk, m_wv, m_ax, m_awq, m_oa, m_awo, m_ox, m_wo;
    make_map(enc, &m_bx, B_x, 512, 2048, 64, 128);
    make_map(enc, &m_wq, B_Wq, 4096, 512, 64, 64);
    make_map(enc, &m_wk, B_Wk, 4096, 512, 64, 64);
    make_map(enc, &m_wv, B_Wv, 4096, 512, 64, 64);
    make_map(enc, &m_ax, A_x, 512, 2048, 64, 128);
    make_map(enc, &m_awq, A_wq, 512, 512, 64, 64);
    make_map(enc, &m_oa, p_oa, 512, 2048, 64, 128);
    make_map(enc, &m_awo, A_wo, 512, 512, 64, 64);
    make_map(enc, &m_ox, p_ox, 4096, 2048, 64, 128);
    make_map(enc, &m_wo, B_Wo, 512, 4096, 64, 64);
    CUtensorMap m_ox64;
    make_map(enc, &m_ox64, p_ox, 4096, 2048, 64, 64);

    cudaStream_t s0 = cudaStreamPerThread;
    cudaEventRecord(e0, s0);
    cudaStreamWaitEvent(s1, e0, 0);

    rec_kernel<<<64, 256, R_SMEM, s0>>>(m_wq, m_wk, m_wv, m_wo, B_mem0, B_x, out);

    gemm_proj<<<(nsm > 96 ? nsm - 64 : 32), 352, P_SMEM, s1>>>(m_bx, m_wq, m_wk, m_wv, m_ax, m_awq, A_x, A_wk, A_wv);
    attn_a_kernel<<<512, 128, 0, s1>>>();
    cudaEventRecord(e3, s1);
    cudaLaunchConfig_t cfg = {};
    cfg.gridDim = dim3(4 * OG_Q1); cfg.blockDim = dim3(128); cfg.dynamicSmemBytes = W_SMEM; cfg.stream = s1;
    cudaLaunchAttribute at[1];
    at[0].id = cudaLaunchAttributeProgrammaticStreamSerialization;
    at[0].val.programmaticStreamSerializationAllowed = 1;
    cfg.attrs = at; cfg.numAttrs = 1;
    cudaLaunchKernelEx(&cfg, gemm_wg<2>, m_ox, m_wo, m_ox64, m_wo, out + 512, 1024, 0, 4);
    cudaStreamWaitEvent(s2, e3, 0);
    gemm_wg<0><<<64, 128, W_SMEM, s2>>>(m_oa, m_awo, m_awo, m_awo, out, 1024, 8, 4);
    cudaEventRecord(e4, s2);
    cfg.gridDim = dim3(288 - 4 * NS1 - 4 * OG_Q1); cfg.stream = s2;
    cudaLaunchKernelEx(&cfg, gemm_wg<2>, m_ox, m_wo, m_ox64, m_wo, out + 512, 1024, OG_Q1, 4);
    cudaEventRecord(e2, s2);
    cudaEventRecord(e1, s1);
    cudaStreamWaitEvent(s0, e1, 0);
    cudaStreamWaitEvent(s0, e2, 0);
    cudaStreamWaitEvent(s0, e4, 0);
}
```
